```python
import torch

def _softmax(x, axis=-1):
    return torch.softmax(x, dim=axis)
def _gelu(x):
    return torch.nn.functional.gelu(x, approximate="tanh")
def _silu(x):
    return torch.nn.functional.silu(x)
def _sigmoid(x):
    return torch.sigmoid(x)
def _layernorm(x, axis=-1, eps=1e-5):
    m = x.mean(dim=axis, keepdim=True)
    v = x.var(dim=axis, keepdim=True, unbiased=False)
    return (x - m) / torch.sqrt(v + eps)
def _scatter_add(tgt, idx, src, axis=0):
    return tgt.clone().index_add_(axis, idx, src)
def _segment_sum(src, seg, n):
    out = torch.zeros((n,) + src.shape[1:], dtype=src.dtype)
    return out.index_add_(0, seg, src)
def _pad(x, pw):
    flat = tuple(v for pair in reversed(pw) for v in pair)
    return torch.nn.functional.pad(x, flat)

kernel_name = 'gated_mix__mha_block__ssm_conv_s4__prompt'

def setup_inputs():

    _w = (lambda a: (lambda t: t.to(torch.bfloat16) if t.is_floating_point() else t)(torch.as_tensor(a)))
    def _A_setup():
        B, S, D, H = 1, 2048, 576, 32
        return {
            "x": _w((lambda *s: torch.randn(*s, dtype=torch.bfloat16) * 0.05)(B, S, D)),
            "wqkv": _w((lambda *s: torch.randn(*s, dtype=torch.bfloat16) * 0.8)(D, 3 * D)),
            "wo": _w((lambda *s: torch.randn(*s, dtype=torch.bfloat16) * 0.05)(D, D)),
        }
    _A_in = _A_setup()

    def _B_setup():
        B, L, D, N = 1, 2048, 576, 128
        A_re = -(lambda _x: torch.exp(torch.as_tensor(_x)))((lambda *s: torch.randn(*s, dtype=torch.bfloat16) * 6.4)(D, N))
        A_im = torch.pi * (lambda *s: torch.randn(*s, dtype=torch.bfloat16) * 0.1)(D, N)
        B_re = (lambda *s: torch.randn(*s, dtype=torch.bfloat16) * 0.2)(D, N)
        B_im = (lambda *s: torch.randn(*s, dtype=torch.bfloat16) * 0.2)(D, N)
        C_re = (lambda *s: torch.randn(*s, dtype=torch.bfloat16) * 0.2)(D, N)
        C_im = (lambda *s: torch.randn(*s, dtype=torch.bfloat16) * 0.2)(D, N)
        log_dt = (lambda *s: torch.randn(*s, dtype=torch.bfloat16) * 0.1)(D) * 0.5 - 4.0
        Dskip = (lambda *s: torch.randn(*s, dtype=torch.bfloat16) * 0.1)(D)
        return {
            "u": _w((lambda *s: torch.randn(*s, dtype=torch.bfloat16) * 0.05)(B, L, D)),
            "A_re": _w(A_re),
            "A_im": _w(A_im),
            "B_re": _w(B_re),
            "B_im": _w(B_im),
            "C_re": _w(C_re),
            "C_im": _w(C_im),
            "log_dt": _w(log_dt),
            "Dskip": _w(Dskip),
        }
    _B_in = _B_setup()

    return {
        "A_x": _A_in["x"],
        "A_wqkv": _A_in["wqkv"],
        "A_wo": _A_in["wo"],
        "B_u": _B_in["u"],
        "B_A_re": _B_in["A_re"],
        "B_A_im": _B_in["A_im"],
        "B_B_re": _B_in["B_re"],
        "B_B_im": _B_in["B_im"],
        "B_C_re": _B_in["C_re"],
        "B_C_im": _B_in["C_im"],
        "B_log_dt": _B_in["log_dt"],
        "B_Dskip": _B_in["Dskip"],
        "gate_w": _w((lambda *s: torch.randn(*s, dtype=torch.bfloat16) * 0.05)(576) * 16.0),
    }

def reference(A_x, A_wqkv, A_wo, B_u, B_A_re, B_A_im, B_B_re, B_B_im, B_C_re, B_C_im, B_log_dt, B_Dskip, gate_w):
    def _A_ref(x, wqkv, wo):
        B, S, D = x.shape
        H = 32
        Dh = D // H
        qkv = (lambda x, *d: x.permute(*d))((x @ wqkv).reshape(B, S, 3, H, Dh), 2, 0, 3, 1, 4)
        q, k, v = qkv[0], qkv[1], qkv[2]
        scores = torch.einsum("bhqd,bhkd->bhqk", q, k) * (Dh ** -0.5)
        p = _softmax(scores, axis=-1)
        o = torch.einsum("bhqk,bhkd->bhqd", p, v)
        return (lambda x, *d: x.permute(*d))(o, 0, 2, 1, 3).reshape(B, S, D) @ wo

    def _B_ref(u, A_re, A_im, B_re, B_im, C_re, C_im, log_dt, Dskip):
        Bsz, L, D = u.shape
        dt = torch.exp(log_dt)[:, None]
        A = A_re + 1j * A_im
        Bc = B_re + 1j * B_im
        Cc = C_re + 1j * C_im
        logdA = dt * A
        dB = dt * Bc
        l = (lambda x, dt: x.to(dt))(torch.arange(L), A_re.dtype)
        P = torch.exp(logdA[:, :, None] * l[None, None, :])
        K = torch.einsum("dn,dnl,dn->dl", Cc, P, dB).real
        L2 = 2 * L
        Kp = _pad(K, ((0, 0), (0, L)))
        up = (lambda x, *d: x.permute(*d))(u, 0, 2, 1)
        up = _pad(up, ((0, 0), (0, 0), (0, L)))
        Kf = (lambda x, axes=(-2,-1): torch.fft.rfft2(x.float(), dim=axes))(Kp[:, None, :], axes=(-2, -1))
        Uf = (lambda x, axes=(-2,-1): torch.fft.rfft2(x.float(), dim=axes))(up[:, :, None, :], axes=(-2, -1))
        Yf = Uf * Kf[None, :, :, :]
        y = (lambda x, s, axes=(-2,-1): torch.fft.irfft2(x, s=s, dim=axes).to(torch.bfloat16))(Yf, (1, L2), axes=(-2, -1))[:, :, 0, :L]
        y = (lambda x, *d: x.permute(*d))(y, 0, 2, 1) + u * Dskip[None, None, :]
        return y

    x = A_x
    g = _sigmoid((x * gate_w).sum(-1, keepdims=True))
    a = _A_ref(x, A_wqkv, A_wo)
    b = _B_ref(x, B_A_re, B_A_im, B_B_re, B_B_im, B_C_re, B_C_im, B_log_dt, B_Dskip)
    return g * a + (1 - g) * b
```

```cpp
#include <cuda_runtime.h>
#include <cuda_bf16.h>
#include <cuda.h>
#include <stdint.h>

namespace {

constexpr int SEQ = 2048, DM = 576, NHEAD = 32, DH = 18;

constexpr int SLOT_BYTES = 256 * 384;
__device__ __align__(1024) uint8_t g_qkv[96 * SLOT_BYTES];
__device__ float g_kn[2 * 32 * 64];
__device__ float g_gatep[8 * SEQ];
__device__ __align__(128) uint8_t g_U[DM * 4096];
constexpr int R_WORDS = 2064;
constexpr int FB_BYTES = 1296;
__device__ __align__(128) uint8_t g_Fb[512 * FB_BYTES];
constexpr int WOT_BYTES = 72 * 9 * 128;
__device__ __align__(128) uint8_t g_woT[8 * WOT_BYTES];
__device__ __align__(128) uint8_t g_O[8 * 256 * 1152];
__device__ __align__(128) __nv_bfloat16 g_bT[DM * SEQ];

#define TSTAMP(k, slot) do { } while (0)
#define CSTAMP(k, slot) do { } while (0)

__device__ __forceinline__ uint32_t smem_u32(const void* p) { return (uint32_t)__cvta_generic_to_shared(p); }
__device__ __forceinline__ void mbar_init(uint32_t bar, uint32_t cnt) {
    asm volatile("mbarrier.init.shared::cta.b64 [%0], %1;" ::"r"(bar), "r"(cnt) : "memory");
}
__device__ __forceinline__ void mbar_init_fence() { asm volatile("fence.mbarrier_init.release.cluster;" ::: "memory"); }
__device__ __forceinline__ void mbar_expect_tx(uint32_t bar, uint32_t bytes) {
    asm volatile("mbarrier.arrive.expect_tx.shared::cta.b64 _, [%0], %1;" ::"r"(bar), "r"(bytes) : "memory");
}
__device__ __forceinline__ void mbar_arrive(uint32_t bar) {
    asm volatile("mbarrier.arrive.shared::cta.b64 _, [%0];" ::"r"(bar) : "memory");
}
__device__ __forceinline__ bool mbar_try(uint32_t bar, uint32_t parity) {
    uint32_t ok;
    asm volatile("{\n.reg .pred p;\nmbarrier.try_wait.parity.shared::cta.b64 p, [%1], %2;\nselp.u32 %0, 1, 0, p;\n}"
                 : "=r"(ok) : "r"(bar), "r"(parity) : "memory");
    return ok != 0;
}
__device__ __forceinline__ void mbar_wait(uint32_t bar, uint32_t parity) {
    if (mbar_try(bar, parity)) return;
    int n = 0;
    while (!mbar_try(bar, parity)) {
        if (++n > (1 << 22)) __trap();
    }
}
__device__ __forceinline__ void mbar_wait_warp(uint32_t bar, uint32_t parity) {
    int n = 0;
    while (!__all_sync(0xffffffffu, mbar_try(bar, parity))) {
        if (++n > (1 << 22)) __trap();
    }
}
__device__ __forceinline__ void tma_load_2d(uint32_t dst, const CUtensorMap* tm, int c0, int c1, uint32_t bar) {
    asm volatile("cp.async.bulk.tensor.2d.shared::cluster.global.mbarrier::complete_tx::bytes [%0], [%1, {%3, %4}], [%2];"
                 ::"r"(dst), "l"(tm), "r"(bar), "r"(c0), "r"(c1) : "memory");
}
__device__ __forceinline__ void bulk_g2s(uint32_t dst, const void* src, uint32_t bytes, uint32_t bar) {
    asm volatile("cp.async.bulk.shared::cluster.global.mbarrier::complete_tx::bytes [%0], [%1], %2, [%3];"
                 ::"r"(dst), "l"(src), "r"(bytes), "r"(bar) : "memory");
}
__device__ __forceinline__ void bulk_s2g(void* dst, uint32_t src, uint32_t bytes) {
    asm volatile("cp.async.bulk.global.shared::cta.bulk_group [%0], [%1], %2;" ::"l"(dst), "r"(src), "r"(bytes) : "memory");
}
__device__ __forceinline__ void bulk_prefetch_l2(const void* src, uint32_t bytes) {
    asm volatile("cp.async.bulk.prefetch.L2.global [%0], %1;" ::"l"(src), "r"(bytes) : "memory");
}
__device__ __forceinline__ void bulk_commit() { asm volatile("cp.async.bulk.commit_group;" ::: "memory"); }
__device__ __forceinline__ void bulk_wait0() { asm volatile("cp.async.bulk.wait_group 0;" ::: "memory"); }
__device__ __forceinline__ void fence_async() { asm volatile("fence.proxy.async.shared::cta;" ::: "memory"); }
__device__ __forceinline__ void fence_proxy_all() { asm volatile("fence.proxy.async;" ::: "memory"); }
__device__ __forceinline__ void cp_async16(uint32_t dst, const void* src) {
    asm volatile("cp.async.cg.shared.global [%0], [%1], 16;" ::"r"(dst), "l"(src) : "memory");
}
__device__ __forceinline__ void cp_async_mbar_arrive(uint32_t bar) {
    asm volatile("cp.async.mbarrier.arrive.noinc.shared::cta.b64 [%0];" ::"r"(bar) : "memory");
}
__device__ __forceinline__ void prefetch_l2(const void* p) { asm volatile("prefetch.global.L2 [%0];" ::"l"(p)); }
__device__ __forceinline__ void cp_async_wait_all() { asm volatile("cp.async.wait_all;" ::: "memory"); }
__device__ __forceinline__ void named_bar(int id, int n) { asm volatile("bar.sync %0, %1;" ::"r"(id), "r"(n) : "memory"); }
__device__ __forceinline__ void pdl_wait() { asm volatile("griddepcontrol.wait;" ::: "memory"); }
__device__ __forceinline__ void pdl_launch() { asm volatile("griddepcontrol.launch_dependents;" ::: "memory"); }

__device__ __forceinline__ int uniform_wg() {
    return (__all_sync(0xffffffffu, (threadIdx.x & 256) != 0) ? 2 : 0) + (__all_sync(0xffffffffu, (threadIdx.x & 128) != 0) ? 1 : 0);
}
__device__ __forceinline__ void wg_fence() { asm volatile("wgmma.fence.sync.aligned;" ::: "memory"); }
__device__ __forceinline__ void wg_commit() { asm volatile("wgmma.commit_group.sync.aligned;" ::: "memory"); }
template <int N> __device__ __forceinline__ void wg_wait() { asm volatile("wgmma.wait_group.sync.aligned %0;" ::"n"(N) : "memory"); }
template <int N> __device__ __forceinline__ void fence_regs(float (&s)[N]) {
#pragma unroll
    for (int i = 0; i < N; i++) asm volatile("" : "+f"(s[i])::"memory");
}
template <int N> __device__ __forceinline__ void fence_regs(uint32_t (&s)[N]) {
#pragma unroll
    for (int i = 0; i < N; i++) asm volatile("" : "+r"(s[i])::"memory");
}
__device__ __forceinline__ uint64_t mkdesc(uint32_t addr, uint32_t lbo, uint32_t sbo, uint32_t swz) {
    return (uint64_t)((addr & 0x3FFFF) >> 4) | ((uint64_t)(lbo >> 4) << 16) | ((uint64_t)(sbo >> 4) << 32) | ((uint64_t)swz << 62);
}

__device__ __forceinline__ uint32_t pack_bf16(float lo, float hi) {
    uint32_t r;
    asm("cvt.rn.bf16x2.f32 %0, %1, %2;" : "=r"(r) : "f"(hi), "f"(lo));
    return r;
}
__device__ __forceinline__ float bf16r(float x) { return __bfloat162float(__float2bfloat16_rn(x)); }
__device__ __forceinline__ float bf_lo(uint32_t w) { return __uint_as_float(w << 16); }
__device__ __forceinline__ float bf_hi(uint32_t w) { return __uint_as_float(w & 0xFFFF0000u); }
__device__ __forceinline__ float ex2f(float a) { float r; asm("ex2.approx.ftz.f32 %0, %1;" : "=f"(r) : "f"(a)); return r; }
__device__ __forceinline__ float sinf_a(float a) { float r; asm("sin.approx.ftz.f32 %0, %1;" : "=f"(r) : "f"(a)); return r; }
__device__ __forceinline__ float cosf_a(float a) { float r; asm("cos.approx.ftz.f32 %0, %1;" : "=f"(r) : "f"(a)); return r; }
__device__ __forceinline__ uint32_t prmt(uint32_t a, uint32_t b, uint32_t s) {
    uint32_t r;
    asm("prmt.b32 %0, %1, %2, %3;" : "=r"(r) : "r"(a), "r"(b), "r"(s));
    return r;
}
__device__ __forceinline__ uint32_t hfma_bf(uint32_t a, uint32_t b, uint32_t c) {
    uint32_t r;
    asm("fma.rn.bf16x2 %0, %1, %2, %3;" : "=r"(r) : "r"(a), "r"(b), "r"(c));
    return r;
}
__device__ __forceinline__ uint32_t hmul_bf(uint32_t a, uint32_t b) {
    uint32_t r;
    asm("mul.rn.bf16x2 %0, %1, %2;" : "=r"(r) : "r"(a), "r"(b));
    return r;
}
__device__ __forceinline__ uint32_t hadd_bf(uint32_t a, uint32_t b) {
    uint32_t r;
    asm("add.rn.bf16x2 %0, %1, %2;" : "=r"(r) : "r"(a), "r"(b));
    return r;
}
template <int LUT> __device__ __forceinline__ uint32_t lop3(uint32_t a, uint32_t b, uint32_t c) {
    uint32_t r;
    asm("lop3.b32 %0, %1, %2, %3, %4;" : "=r"(r) : "r"(a), "r"(b), "r"(c), "n"(LUT));
    return r;
}

__device__ __forceinline__ void wg_ss_n224_tb(float (&d)[112], uint64_t da, uint64_t db, int sd) {
    asm volatile("{\n.reg .pred p;\nsetp.ne.b32 p, %114, 0;\n"
        "wgmma.mma_async.sync.aligned.m64n224k16.f32.bf16.bf16 "
        "{%0, %1, %2, %3, %4, %5, %6, %7, %8, %9, %10, %11, %12, %13, %14, %15, %16, %17, %18, %19, %20, %21, %22, %23, %24, %25, %26, %27, %28, %29, %30, %31, %32, %33, %34, %35, %36, %37, %38, %39, %40, %41, %42, %43, %44, %45, %46, %47, %48, %49, %50, %51, %52, %53, %54, %55, %56, %57, %58, %59, %60, %61, %62, %63, %64, %65, %66, %67, %68, %69, %70, %71, %72, %73, %74, %75, %76, %77, %78, %79, %80, %81, %82, %83, %84, %85, %86, %87, %88, %89, %90, %91, %92, %93, %94, %95, %96, %97, %98, %99, %100, %101, %102, %103, %104, %105, %106, %107, %108, %109, %110, %111}, %112, %113, p, 1, 1, 0, 1;\n}\n"
        : "+f"(d[0]), "+f"(d[1]), "+f"(d[2]), "+f"(d[3]), "+f"(d[4]), "+f"(d[5]), "+f"(d[6]), "+f"(d[7]), "+f"(d[8]), "+f"(d[9]), "+f"(d[10]), "+f"(d[11]), "+f"(d[12]), "+f"(d[13]), "+f"(d[14]), "+f"(d[15]), "+f"(d[16]), "+f"(d[17]), "+f"(d[18]), "+f"(d[19]), "+f"(d[20]), "+f"(d[21]), "+f"(d[22]), "+f"(d[23]), "+f"(d[24]), "+f"(d[25]), "+f"(d[26]), "+f"(d[27]), "+f"(d[28]), "+f"(d[29]), "+f"(d[30]), "+f"(d[31]), "+f"(d[32]), "+f"(d[33]), "+f"(d[34]), "+f"(d[35]), "+f"(d[36]), "+f"(d[37]), "+f"(d[38]), "+f"(d[39]), "+f"(d[40]), "+f"(d[41]), "+f"(d[42]), "+f"(d[43]), "+f"(d[44]), "+f"(d[45]), "+f"(d[46]), "+f"(d[47]), "+f"(d[48]), "+f"(d[49]), "+f"(d[50]), "+f"(d[51]), "+f"(d[52]), "+f"(d[53]), "+f"(d[54]), "+f"(d[55]), "+f"(d[56]), "+f"(d[57]), "+f"(d[58]), "+f"(d[59]), "+f"(d[60]), "+f"(d[61]), "+f"(d[62]), "+f"(d[63]), "+f"(d[64]), "+f"(d[65]), "+f"(d[66]), "+f"(d[67]), "+f"(d[68]), "+f"(d[69]), "+f"(d[70]), "+f"(d[71]), "+f"(d[72]), "+f"(d[73]), "+f"(d[74]), "+f"(d[75]), "+f"(d[76]), "+f"(d[77]), "+f"(d[78]), "+f"(d[79]), "+f"(d[80]), "+f"(d[81]), "+f"(d[82]), "+f"(d[83]), "+f"(d[84]), "+f"(d[85]), "+f"(d[86]), "+f"(d[87]), "+f"(d[88]), "+f"(d[89]), "+f"(d[90]), "+f"(d[91]), "+f"(d[92]), "+f"(d[93]), "+f"(d[94]), "+f"(d[95]), "+f"(d[96]), "+f"(d[97]), "+f"(d[98]), "+f"(d[99]), "+f"(d[100]), "+f"(d[101]), "+f"(d[102]), "+f"(d[103]), "+f"(d[104]), "+f"(d[105]), "+f"(d[106]), "+f"(d[107]), "+f"(d[108]), "+f"(d[109]), "+f"(d[110]), "+f"(d[111])
        : "l"(da), "l"(db), "r"(sd));
}

__device__ __forceinline__ void wg_ss_n256_tb(float (&d)[128], uint64_t da, uint64_t db, int sd) {
    asm volatile("{\n.reg .pred p;\nsetp.ne.b32 p, %130, 0;\n"
        "wgmma.mma_async.sync.aligned.m64n256k16.f32.bf16.bf16 "
        "{%0, %1, %2, %3, %4, %5, %6, %7, %8, %9, %10, %11, %12, %13, %14, %15, %16, %17, %18, %19, %20, %21, %22, %23, %24, %25, %26, %27, %28, %29, %30, %31, %32, %33, %34, %35, %36, %37, %38, %39, %40, %41, %42, %43, %44, %45, %46, %47, %48, %49, %50, %51, %52, %53, %54, %55, %56, %57, %58, %59, %60, %61, %62, %63, %64, %65, %66, %67, %68, %69, %70, %71, %72, %73, %74, %75, %76, %77, %78, %79, %80, %81, %82, %83, %84, %85, %86, %87, %88, %89, %90, %91, %92, %93, %94, %95, %96, %97, %98, %99, %100, %101, %102, %103, %104, %105, %106, %107, %108, %109, %110, %111, %112, %113, %114, %115, %116, %117, %118, %119, %120, %121, %122, %123, %124, %125, %126, %127}, %128, %129, p, 1, 1, 0, 1;\n}\n"
        : "+f"(d[0]), "+f"(d[1]), "+f"(d[2]), "+f"(d[3]), "+f"(d[4]), "+f"(d[5]), "+f"(d[6]), "+f"(d[7]), "+f"(d[8]), "+f"(d[9]), "+f"(d[10]), "+f"(d[11]), "+f"(d[12]), "+f"(d[13]), "+f"(d[14]), "+f"(d[15]), "+f"(d[16]), "+f"(d[17]), "+f"(d[18]), "+f"(d[19]), "+f"(d[20]), "+f"(d[21]), "+f"(d[22]), "+f"(d[23]), "+f"(d[24]), "+f"(d[25]), "+f"(d[26]), "+f"(d[27]), "+f"(d[28]), "+f"(d[29]), "+f"(d[30]), "+f"(d[31]), "+f"(d[32]), "+f"(d[33]), "+f"(d[34]), "+f"(d[35]), "+f"(d[36]), "+f"(d[37]), "+f"(d[38]), "+f"(d[39]), "+f"(d[40]), "+f"(d[41]), "+f"(d[42]), "+f"(d[43]), "+f"(d[44]), "+f"(d[45]), "+f"(d[46]), "+f"(d[47]), "+f"(d[48]), "+f"(d[49]), "+f"(d[50]), "+f"(d[51]), "+f"(d[52]), "+f"(d[53]), "+f"(d[54]), "+f"(d[55]), "+f"(d[56]), "+f"(d[57]), "+f"(d[58]), "+f"(d[59]), "+f"(d[60]), "+f"(d[61]), "+f"(d[62]), "+f"(d[63]), "+f"(d[64]), "+f"(d[65]), "+f"(d[66]), "+f"(d[67]), "+f"(d[68]), "+f"(d[69]), "+f"(d[70]), "+f"(d[71]), "+f"(d[72]), "+f"(d[73]), "+f"(d[74]), "+f"(d[75]), "+f"(d[76]), "+f"(d[77]), "+f"(d[78]), "+f"(d[79]), "+f"(d[80]), "+f"(d[81]), "+f"(d[82]), "+f"(d[83]), "+f"(d[84]), "+f"(d[85]), "+f"(d[86]), "+f"(d[87]), "+f"(d[88]), "+f"(d[89]), "+f"(d[90]), "+f"(d[91]), "+f"(d[92]), "+f"(d[93]), "+f"(d[94]), "+f"(d[95]), "+f"(d[96]), "+f"(d[97]), "+f"(d[98]), "+f"(d[99]), "+f"(d[100]), "+f"(d[101]), "+f"(d[102]), "+f"(d[103]), "+f"(d[104]), "+f"(d[105]), "+f"(d[106]), "+f"(d[107]), "+f"(d[108]), "+f"(d[109]), "+f"(d[110]), "+f"(d[111]), "+f"(d[112]), "+f"(d[113]), "+f"(d[114]), "+f"(d[115]), "+f"(d[116]), "+f"(d[117]), "+f"(d[118]), "+f"(d[119]), "+f"(d[120]), "+f"(d[121]), "+f"(d[122]), "+f"(d[123]), "+f"(d[124]), "+f"(d[125]), "+f"(d[126]), "+f"(d[127])
        : "l"(da), "l"(db), "r"(sd));
}

__device__ __forceinline__ void wg_ss_n72_tb(float (&d)[36], uint64_t da, uint64_t db, int sd) {
    asm volatile("{\n.reg .pred p;\nsetp.ne.b32 p, %38, 0;\n"
        "wgmma.mma_async.sync.aligned.m64n72k16.f32.bf16.bf16 "
        "{%0, %1, %2, %3, %4, %5, %6, %7, %8, %9, %10, %11, %12, %13, %14, %15, %16, %17, %18, %19, %20, %21, %22, %23, %24, %25, %26, %27, %28, %29, %30, %31, %32, %33, %34, %35}, %36, %37, p, 1, 1, 0, 1;\n}\n"
        : "+f"(d[0]), "+f"(d[1]), "+f"(d[2]), "+f"(d[3]), "+f"(d[4]), "+f"(d[5]), "+f"(d[6]), "+f"(d[7]), "+f"(d[8]), "+f"(d[9]), "+f"(d[10]), "+f"(d[11]), "+f"(d[12]), "+f"(d[13]), "+f"(d[14]), "+f"(d[15]), "+f"(d[16]), "+f"(d[17]), "+f"(d[18]), "+f"(d[19]), "+f"(d[20]), "+f"(d[21]), "+f"(d[22]), "+f"(d[23]), "+f"(d[24]), "+f"(d[25]), "+f"(d[26]), "+f"(d[27]), "+f"(d[28]), "+f"(d[29]), "+f"(d[30]), "+f"(d[31]), "+f"(d[32]), "+f"(d[33]), "+f"(d[34]), "+f"(d[35])
        : "l"(da), "l"(db), "r"(sd));
}

__device__ __forceinline__ void wg_qk_n64_first(float (&d)[32], uint32_t a0, uint32_t a1, uint32_t a2, uint32_t a3, uint64_t db) {
    asm volatile("wgmma.mma_async.sync.aligned.m64n64k16.f32.bf16.bf16 "
        "{%0, %1, %2, %3, %4, %5, %6, %7, %8, %9, %10, %11, %12, %13, %14, %15, %16, %17, %18, %19, %20, %21, %22, %23, %24, %25, %26, %27, %28, %29, %30, %31}, {%32, %33, %34, %35}, %36, 0, 1, 1, 0;\n"
        : "=f"(d[0]), "=f"(d[1]), "=f"(d[2]), "=f"(d[3]), "=f"(d[4]), "=f"(d[5]), "=f"(d[6]), "=f"(d[7]), "=f"(d[8]), "=f"(d[9]), "=f"(d[10]), "=f"(d[11]), "=f"(d[12]), "=f"(d[13]), "=f"(d[14]), "=f"(d[15]), "=f"(d[16]), "=f"(d[17]), "=f"(d[18]), "=f"(d[19]), "=f"(d[20]), "=f"(d[21]), "=f"(d[22]), "=f"(d[23]), "=f"(d[24]), "=f"(d[25]), "=f"(d[26]), "=f"(d[27]), "=f"(d[28]), "=f"(d[29]), "=f"(d[30]), "=f"(d[31])
        : "r"(a0), "r"(a1), "r"(a2), "r"(a3), "l"(db));
}

__device__ __forceinline__ void wg_qk_n64_acc(float (&d)[32], uint32_t a0, uint32_t a1, uint32_t a2, uint32_t a3, uint64_t db) {
    asm volatile("wgmma.mma_async.sync.aligned.m64n64k16.f32.bf16.bf16 "
        "{%0, %1, %2, %3, %4, %5, %6, %7, %8, %9, %10, %11, %12, %13, %14, %15, %16, %17, %18, %19, %20, %21, %22, %23, %24, %25, %26, %27, %28, %29, %30, %31}, {%32, %33, %34, %35}, %36, 1, 1, 1, 0;\n"
        : "+f"(d[0]), "+f"(d[1]), "+f"(d[2]), "+f"(d[3]), "+f"(d[4]), "+f"(d[5]), "+f"(d[6]), "+f"(d[7]), "+f"(d[8]), "+f"(d[9]), "+f"(d[10]), "+f"(d[11]), "+f"(d[12]), "+f"(d[13]), "+f"(d[14]), "+f"(d[15]), "+f"(d[16]), "+f"(d[17]), "+f"(d[18]), "+f"(d[19]), "+f"(d[20]), "+f"(d[21]), "+f"(d[22]), "+f"(d[23]), "+f"(d[24]), "+f"(d[25]), "+f"(d[26]), "+f"(d[27]), "+f"(d[28]), "+f"(d[29]), "+f"(d[30]), "+f"(d[31])
        : "r"(a0), "r"(a1), "r"(a2), "r"(a3), "l"(db));
}

__device__ __forceinline__ void wg_qk_n96_first(float (&d)[48], uint32_t a0, uint32_t a1, uint32_t a2, uint32_t a3, uint64_t db) {
    asm volatile("wgmma.mma_async.sync.aligned.m64n96k16.f32.bf16.bf16 "
        "{%0, %1, %2, %3, %4, %5, %6, %7, %8, %9, %10, %11, %12, %13, %14, %15, %16, %17, %18, %19, %20, %21, %22, %23, %24, %25, %26, %27, %28, %29, %30, %31, %32, %33, %34, %35, %36, %37, %38, %39, %40, %41, %42, %43, %44, %45, %46, %47}, {%48, %49, %50, %51}, %52, 0, 1, 1, 0;\n"
        : "=f"(d[0]), "=f"(d[1]), "=f"(d[2]), "=f"(d[3]), "=f"(d[4]), "=f"(d[5]), "=f"(d[6]), "=f"(d[7]), "=f"(d[8]), "=f"(d[9]), "=f"(d[10]), "=f"(d[11]), "=f"(d[12]), "=f"(d[13]), "=f"(d[14]), "=f"(d[15]), "=f"(d[16]), "=f"(d[17]), "=f"(d[18]), "=f"(d[19]), "=f"(d[20]), "=f"(d[21]), "=f"(d[22]), "=f"(d[23]), "=f"(d[24]), "=f"(d[25]), "=f"(d[26]), "=f"(d[27]), "=f"(d[28]), "=f"(d[29]), "=f"(d[30]), "=f"(d[31]), "=f"(d[32]), "=f"(d[33]), "=f"(d[34]), "=f"(d[35]), "=f"(d[36]), "=f"(d[37]), "=f"(d[38]), "=f"(d[39]), "=f"(d[40]), "=f"(d[41]), "=f"(d[42]), "=f"(d[43]), "=f"(d[44]), "=f"(d[45]), "=f"(d[46]), "=f"(d[47])
        : "r"(a0), "r"(a1), "r"(a2), "r"(a3), "l"(db));
}

__device__ __forceinline__ void wg_qk_n96_acc(float (&d)[48], uint32_t a0, uint32_t a1, uint32_t a2, uint32_t a3, uint64_t db) {
    asm volatile("wgmma.mma_async.sync.aligned.m64n96k16.f32.bf16.bf16 "
        "{%0, %1, %2, %3, %4, %5, %6, %7, %8, %9, %10, %11, %12, %13, %14, %15, %16, %17, %18, %19, %20, %21, %22, %23, %24, %25, %26, %27, %28, %29, %30, %31, %32, %33, %34, %35, %36, %37, %38, %39, %40, %41, %42, %43, %44, %45, %46, %47}, {%48, %49, %50, %51}, %52, 1, 1, 1, 0;\n"
        : "+f"(d[0]), "+f"(d[1]), "+f"(d[2]), "+f"(d[3]), "+f"(d[4]), "+f"(d[5]), "+f"(d[6]), "+f"(d[7]), "+f"(d[8]), "+f"(d[9]), "+f"(d[10]), "+f"(d[11]), "+f"(d[12]), "+f"(d[13]), "+f"(d[14]), "+f"(d[15]), "+f"(d[16]), "+f"(d[17]), "+f"(d[18]), "+f"(d[19]), "+f"(d[20]), "+f"(d[21]), "+f"(d[22]), "+f"(d[23]), "+f"(d[24]), "+f"(d[25]), "+f"(d[26]), "+f"(d[27]), "+f"(d[28]), "+f"(d[29]), "+f"(d[30]), "+f"(d[31]), "+f"(d[32]), "+f"(d[33]), "+f"(d[34]), "+f"(d[35]), "+f"(d[36]), "+f"(d[37]), "+f"(d[38]), "+f"(d[39]), "+f"(d[40]), "+f"(d[41]), "+f"(d[42]), "+f"(d[43]), "+f"(d[44]), "+f"(d[45]), "+f"(d[46]), "+f"(d[47])
        : "r"(a0), "r"(a1), "r"(a2), "r"(a3), "l"(db));
}

__device__ __forceinline__ void wg_qk_n128_first(float (&d)[64], uint32_t a0, uint32_t a1, uint32_t a2, uint32_t a3, uint64_t db) {
    asm volatile("wgmma.mma_async.sync.aligned.m64n128k16.f32.bf16.bf16 "
        "{%0, %1, %2, %3, %4, %5, %6, %7, %8, %9, %10, %11, %12, %13, %14, %15, %16, %17, %18, %19, %20, %21, %22, %23, %24, %25, %26, %27, %28, %29, %30, %31, %32, %33, %34, %35, %36, %37, %38, %39, %40, %41, %42, %43, %44, %45, %46, %47, %48, %49, %50, %51, %52, %53, %54, %55, %56, %57, %58, %59, %60, %61, %62, %63}, {%64, %65, %66, %67}, %68, 0, 1, 1, 0;\n"
        : "=f"(d[0]), "=f"(d[1]), "=f"(d[2]), "=f"(d[3]), "=f"(d[4]), "=f"(d[5]), "=f"(d[6]), "=f"(d[7]), "=f"(d[8]), "=f"(d[9]), "=f"(d[10]), "=f"(d[11]), "=f"(d[12]), "=f"(d[13]), "=f"(d[14]), "=f"(d[15]), "=f"(d[16]), "=f"(d[17]), "=f"(d[18]), "=f"(d[19]), "=f"(d[20]), "=f"(d[21]), "=f"(d[22]), "=f"(d[23]), "=f"(d[24]), "=f"(d[25]), "=f"(d[26]), "=f"(d[27]), "=f"(d[28]), "=f"(d[29]), "=f"(d[30]), "=f"(d[31]), "=f"(d[32]), "=f"(d[33]), "=f"(d[34]), "=f"(d[35]), "=f"(d[36]), "=f"(d[37]), "=f"(d[38]), "=f"(d[39]), "=f"(d[40]), "=f"(d[41]), "=f"(d[42]), "=f"(d[43]), "=f"(d[44]), "=f"(d[45]), "=f"(d[46]), "=f"(d[47]), "=f"(d[48]), "=f"(d[49]), "=f"(d[50]), "=f"(d[51]), "=f"(d[52]), "=f"(d[53]), "=f"(d[54]), "=f"(d[55]), "=f"(d[56]), "=f"(d[57]), "=f"(d[58]), "=f"(d[59]), "=f"(d[60]), "=f"(d[61]), "=f"(d[62]), "=f"(d[63])
        : "r"(a0), "r"(a1), "r"(a2), "r"(a3), "l"(db));
}

__device__ __forceinline__ void wg_qk_n128_acc(float (&d)[64], uint32_t a0, uint32_t a1, uint32_t a2, uint32_t a3, uint64_t db) {
    asm volatile("wgmma.mma_async.sync.aligned.m64n128k16.f32.bf16.bf16 "
        "{%0, %1, %2, %3, %4, %5, %6, %7, %8, %9, %10, %11, %12, %13, %14, %15, %16, %17, %18, %19, %20, %21, %22, %23, %24, %25, %26, %27, %28, %29, %30, %31, %32, %33, %34, %35, %36, %37, %38, %39, %40, %41, %42, %43, %44, %45, %46, %47, %48, %49, %50, %51, %52, %53, %54, %55, %56, %57, %58, %59, %60, %61, %62, %63}, {%64, %65, %66, %67}, %68, 1, 1, 1, 0;\n"
        : "+f"(d[0]), "+f"(d[1]), "+f"(d[2]), "+f"(d[3]), "+f"(d[4]), "+f"(d[5]), "+f"(d[6]), "+f"(d[7]), "+f"(d[8]), "+f"(d[9]), "+f"(d[10]), "+f"(d[11]), "+f"(d[12]), "+f"(d[13]), "+f"(d[14]), "+f"(d[15]), "+f"(d[16]), "+f"(d[17]), "+f"(d[18]), "+f"(d[19]), "+f"(d[20]), "+f"(d[21]), "+f"(d[22]), "+f"(d[23]), "+f"(d[24]), "+f"(d[25]), "+f"(d[26]), "+f"(d[27]), "+f"(d[28]), "+f"(d[29]), "+f"(d[30]), "+f"(d[31]), "+f"(d[32]), "+f"(d[33]), "+f"(d[34]), "+f"(d[35]), "+f"(d[36]), "+f"(d[37]), "+f"(d[38]), "+f"(d[39]), "+f"(d[40]), "+f"(d[41]), "+f"(d[42]), "+f"(d[43]), "+f"(d[44]), "+f"(d[45]), "+f"(d[46]), "+f"(d[47]), "+f"(d[48]), "+f"(d[49]), "+f"(d[50]), "+f"(d[51]), "+f"(d[52]), "+f"(d[53]), "+f"(d[54]), "+f"(d[55]), "+f"(d[56]), "+f"(d[57]), "+f"(d[58]), "+f"(d[59]), "+f"(d[60]), "+f"(d[61]), "+f"(d[62]), "+f"(d[63])
        : "r"(a0), "r"(a1), "r"(a2), "r"(a3), "l"(db));
}

__device__ __forceinline__ void wg_pv_n24(float (&d)[12], uint32_t a0, uint32_t a1, uint32_t a2, uint32_t a3, uint64_t db) {
    asm volatile("wgmma.mma_async.sync.aligned.m64n24k16.f32.bf16.bf16 "
        "{%0, %1, %2, %3, %4, %5, %6, %7, %8, %9, %10, %11}, {%12, %13, %14, %15}, %16, 1, 1, 1, 1;\n"
        : "+f"(d[0]), "+f"(d[1]), "+f"(d[2]), "+f"(d[3]), "+f"(d[4]), "+f"(d[5]), "+f"(d[6]), "+f"(d[7]), "+f"(d[8]), "+f"(d[9]), "+f"(d[10]), "+f"(d[11])
        : "r"(a0), "r"(a1), "r"(a2), "r"(a3), "l"(db));
}

__device__ __forceinline__ void wg_conv_n32(float (&d)[16], uint32_t a0, uint32_t a1, uint32_t a2, uint32_t a3, uint32_t lo) {
    asm volatile("{\n.reg .b64 db;\nmov.b64 db, {%20, 8};\n"
        "wgmma.mma_async.sync.aligned.m64n32k16.f32.bf16.bf16 "
        "{%0, %1, %2, %3, %4, %5, %6, %7, %8, %9, %10, %11, %12, %13, %14, %15}, {%16, %17, %18, %19}, db, 1, 1, 1, 0;\n}\n"
        : "+f"(d[0]), "+f"(d[1]), "+f"(d[2]), "+f"(d[3]), "+f"(d[4]), "+f"(d[5]), "+f"(d[6]), "+f"(d[7]), "+f"(d[8]), "+f"(d[9]), "+f"(d[10]), "+f"(d[11]), "+f"(d[12]), "+f"(d[13]), "+f"(d[14]), "+f"(d[15])
        : "r"(a0), "r"(a1), "r"(a2), "r"(a3), "r"(lo));
}

__device__ __forceinline__ void wg_conv_n32_d64(float (&d)[16], uint32_t a0, uint32_t a1, uint32_t a2, uint32_t a3, uint64_t db) {
    asm volatile("wgmma.mma_async.sync.aligned.m64n32k16.f32.bf16.bf16 "
        "{%0, %1, %2, %3, %4, %5, %6, %7, %8, %9, %10, %11, %12, %13, %14, %15}, {%16, %17, %18, %19}, %20, 1, 1, 1, 0;\n"
        : "+f"(d[0]), "+f"(d[1]), "+f"(d[2]), "+f"(d[3]), "+f"(d[4]), "+f"(d[5]), "+f"(d[6]), "+f"(d[7]), "+f"(d[8]), "+f"(d[9]), "+f"(d[10]), "+f"(d[11]), "+f"(d[12]), "+f"(d[13]), "+f"(d[14]), "+f"(d[15])
        : "r"(a0), "r"(a1), "r"(a2), "r"(a3), "l"(db));
}

constexpr uint32_t MUFU_MASK8 = 0x54;
__host__ __device__ constexpr bool is_mufu(int blk, int half) { return (MUFU_MASK8 >> (2 * (blk & 3) + half)) & 1; }

__device__ __forceinline__ uint32_t exp2_mufu(float x0, float x1) { return pack_bf16(ex2f(x0), ex2f(x1)); }
__device__ __forceinline__ uint32_t exp2_poly(float t0, float t1) {
    const uint32_t H = prmt(__float_as_uint(t0), __float_as_uint(t1), 0x6521);
    const uint32_t F = lop3<0xEA>(H, 0x007F007Fu, 0x3F803F80u);
    uint32_t p = hfma_bf(F, 0x3EB13EB1u, 0xBD22BD22u);
    p = hfma_bf(p, F, 0x3F333F33u);
    return lop3<0xD8>(p, H, 0x7F807F80u);
}

__device__ __forceinline__ void mma_tf32(float (&d)[4], float a0, float a1, float a2, float a3, float b0, float b1) {
    asm volatile("mma.sync.aligned.m16n8k8.row.col.f32.tf32.tf32.f32 {%0,%1,%2,%3}, {%4,%5,%6,%7}, {%8,%9}, {%0,%1,%2,%3};"
                 : "+f"(d[0]), "+f"(d[1]), "+f"(d[2]), "+f"(d[3])
                 : "r"(__float_as_uint(a0)), "r"(__float_as_uint(a1)), "r"(__float_as_uint(a2)), "r"(__float_as_uint(a3)),
                   "r"(__float_as_uint(b0)), "r"(__float_as_uint(b1)));
}
__device__ __forceinline__ void cexp_l(float a2, float b, float l, float& re, float& im) {
    const float m = ex2f(a2 * l);
    const float ph = b * l;
    re = m * cosf_a(ph);
    im = m * sinf_a(ph);
}
__device__ __forceinline__ void cexp_conj(float a2, float b, float l, float& re, float& im) {
    const float m = ex2f(a2 * l);
    const float ph = b * l;
    re = m * cosf_a(ph);
    im = -m * sinf_a(ph);
}

__device__ __forceinline__ float kgen_params(const uint16_t* raw, int rs, float4* par, float dt, int t) {
    const float a = dt * __uint_as_float((uint32_t)raw[t] << 16), b = dt * __uint_as_float((uint32_t)raw[rs + t] << 16);
    const float dbr = dt * __uint_as_float((uint32_t)raw[2 * rs + t] << 16), dbi = dt * __uint_as_float((uint32_t)raw[3 * rs + t] << 16);
    const float cr = __uint_as_float((uint32_t)raw[4 * rs + t] << 16), ci = __uint_as_float((uint32_t)raw[5 * rs + t] << 16);
    const float cbr = cr * dbr - ci * dbi, cbi = cr * dbi + ci * dbr;
    const float a2 = a * 1.4426950408889634f;
    float w64r, w64i, w128r, w128i;
    cexp_l(a2, b, 64.f, w64r, w64i);
    cexp_conj(a2, b, 128.f, w128r, w128i);
    par[2 * t] = make_float4(a2, b, cbr, cbi);
    par[2 * t + 1] = make_float4(w64r, w64i, w128r, w128i);
    float k0 = cbr;
#pragma unroll
    for (int o2 = 16; o2 > 0; o2 >>= 1) k0 += __shfl_xor_sync(0xffffffffu, k0, o2);
    return k0;
}
template <int NU>
__device__ __forceinline__ void kgen_product(const float4* par, float (&D)[NU][5][4], int t) {
    const int w = t >> 5, lane = t & 31, g = lane >> 2, c = lane & 3;
    const float l2 = (float)(g < 4 ? 258 + 2 * g : (g < 6 ? 516 + 4 * (g - 4) : 772 + 4 * (g - 6)));
    const float lf0 = (float)(8 * g), lf1 = (float)(g + 1), lf4 = (float)(1032 + 128 * g);
#pragma unroll
    for (int u = 0; u < NU; u++)
#pragma unroll
        for (int j = 0; j < 5; j++) { D[u][j][0] = D[u][j][1] = D[u][j][2] = D[u][j][3] = 0.f; }
#pragma unroll(NU == 1 ? 2 : 1)
    for (int ks = 0; ks < 8; ks++) {
        const int n = 32 * w + 4 * ks + c;
#pragma unroll
        for (int u = 0; u < NU; u++) {
            const float4 p0 = par[u * 256 + 2 * n], p1 = par[u * 256 + 2 * n + 1];
            float er, ei, x0r, x0i, x2r, x2i, x4r, x4i;
            cexp_l(p0.x, p0.y, lf0, er, ei);
            cexp_conj(p0.x, p0.y, lf1, x0r, x0i);
            cexp_conj(p0.x, p0.y, l2, x2r, x2i);
            cexp_conj(p0.x, p0.y, lf4, x4r, x4i);
            const float y0r = p0.z * er - p0.w * ei, y0i = p0.z * ei + p0.w * er;
            const float y1r = y0r * p1.x - y0i * p1.y, y1i = y0r * p1.y + y0i * p1.x;
            mma_tf32(D[u][0], y0r, y1r, y0i, y1i, x0r, x0i);
            mma_tf32(D[u][2], y0r, y1r, y0i, y1i, x2r, x2i);
            mma_tf32(D[u][4], y0r, y1r, y0i, y1i, x4r, x4i);
            mma_tf32(D[u][1], y0r, y1r, y0i, y1i, x0r * p1.z - x0i * p1.w, x0r * p1.w + x0i * p1.z);
            mma_tf32(D[u][3], y0r, y1r, y0i, y1i, x2r * p1.z - x2i * p1.w, x2r * p1.w + x2i * p1.z);
        }
    }
}
template <int NU>
__device__ __forceinline__ void kgen_sum(const float (&D)[NU][5][4], const float (&k0)[NU], float* Fs, uint8_t* Fb, int fb_stride,
                                         int bar_id, int t) {
    const int w = t >> 5, lane = t & 31, g = lane >> 2, c = lane & 3;
    const int f23_row8 = c < 2 ? 32 : 16, f3_off = c < 2 ? 64 : 32;
#pragma unroll
    for (int u = 0; u < NU; u++) {
        float* Fw = Fs + u * 2576 + w * 644;
        float* f01 = Fw + 2 * c + 1 + 8 * g;
        float* f23 = Fw + (c < 2 ? 257 + 2 * c : (c == 2 ? 385 : 449)) + (c < 2 ? 4 : 2) * g;
        float* f4 = Fw + 513 + 32 * c + g;
        if (lane == 0) Fw[0] = k0[u];
        f01[0] = D[u][0][0]; f01[1] = D[u][0][1]; f01[64] = D[u][0][2]; f01[65] = D[u][0][3];
        f01[128] = D[u][1][0]; f01[129] = D[u][1][1]; f01[192] = D[u][1][2]; f01[193] = D[u][1][3];
        f23[0] = D[u][2][0]; f23[1] = D[u][2][1]; f23[f23_row8] = D[u][2][2]; f23[f23_row8 + 1] = D[u][2][3];
        f23[f3_off] = D[u][3][0]; f23[f3_off + 1] = D[u][3][1]; f23[f3_off + f23_row8] = D[u][3][2]; f23[f3_off + f23_row8 + 1] = D[u][3][3];
        f4[0] = D[u][4][0]; f4[16] = D[u][4][1]; f4[8] = D[u][4][2]; f4[24] = D[u][4][3];
    }
    named_bar(bar_id, 128);
#pragma unroll
    for (int r = 0; r < 2; r++) {
        const int i = t + 128 * r;
        if (i < 161) {
#pragma unroll
            for (int u = 0; u < NU; u++) {
                const float4* f = (const float4*)(Fs + u * 2576) + i;
                const float4 a = f[0], b = f[161], c4 = f[2 * 161], e = f[3 * 161];
                uint2 o;
                o.x = pack_bf16((a.x + b.x) + (c4.x + e.x), (a.y + b.y) + (c4.y + e.y));
                o.y = pack_bf16((a.z + b.z) + (c4.z + e.z), (a.w + b.w) + (c4.w + e.w));
                *(uint2*)(Fb + u * fb_stride + 8 * i) = o;
            }
        }
    }
}
__device__ __forceinline__ void kgen_expand(const uint8_t* Fb, uint8_t* dst, int t) {
    {
        const uint16_t* F = (const uint16_t*)Fb;
        uint4* R4 = (uint4*)(dst + 64) + t;
        uint32_t km, k0_, k1, k2, k3;
        if (t < 64) {
            const uint2 v = *(const uint2*)(F + 4 * t);
            km = t > 0 ? F[4 * t - 1] : 0u;
            R4[0] = make_uint4(prmt(v.x, km, 0x5410), prmt(v.x, v.x, 0x1032), prmt(v.y, v.x, 0x7610), prmt(v.y, v.y, 0x1032));
        } else {
            k0_ = F[128 + 2 * t]; k2 = F[129 + 2 * t]; k3 = F[130 + 2 * t];
            km = t > 64 ? k0_ : F[255];
            R4[0] = make_uint4(prmt(k0_, km, 0x5410), prmt(k0_, k0_, 0x5410), prmt(k2, k0_, 0x5410), prmt(k3, k2, 0x5410));
        }
        k0_ = F[384 + t]; k3 = F[385 + t];
        k2 = (t & 1) ? k3 : k0_;
        R4[128] = make_uint4(prmt(k0_, k0_, 0x5410), prmt(k0_, k0_, 0x5410), prmt(k2, k0_, 0x5410), prmt(k3, k2, 0x5410));
#pragma unroll
        for (int q = 2; q < 4; q++) {
            const int j = 64 * q + (t >> 1);
            const uint32_t fa = F[384 + j], fb = F[385 + j];
            const bool odd = t & 1;
            km = fa;
            k0_ = odd ? ((j & 1) ? fb : fa) : fa;
            k1 = odd ? fb : fa;
            R4[128 * q] = make_uint4(prmt(k0_, km, 0x5410), prmt(k1, k0_, 0x5410), prmt(k1, k1, 0x5410), prmt(k1, k1, 0x5410));
        }
    }
    if (t < 4) *(uint4*)(dst + 16 * t) = make_uint4(0, 0, 0, 0);
}

constexpr int K1_THREADS = 384;
constexpr int K1_STAGES = 3;
constexpr int K1_STAGE = 49152;
constexpr int K1_XS = K1_STAGES * K1_STAGE;
constexpr int K1_US = K1_XS + 128 * 144;
constexpr int K1_WO = K1_US + 72 * 272;
constexpr int K1_GW = K1_WO + 8 * 1168;
constexpr int K1_RAW = K1_GW + 192;
constexpr int K1_PAR = K1_RAW + 6 * 1024;
constexpr int K1_K0 = K1_PAR + 4 * 4096;
constexpr int K1_BAR = K1_K0 + 64;
constexpr int K1_SMEM = K1_BAR + 128;
constexpr int K1_KW = 16 * 6144;
static_assert(K1_BAR % 8 == 0 && K1_SMEM <= 232448, "");

struct K1Params {
    const __nv_bfloat16 *x, *wo, *a_re, *a_im, *b_re, *b_im, *c_re, *c_im, *log_dt, *gate_w;
};

__global__ void __launch_bounds__(K1_THREADS, 1)
k1_qkv(const __grid_constant__ CUtensorMap tmX, const __grid_constant__ CUtensorMap tmW, const __grid_constant__ CUtensorMap tmXs,
       const __grid_constant__ CUtensorMap tmQ8, const __grid_constant__ CUtensorMap tmQ4, const __grid_constant__ CUtensorMap tmQ2,
       const __grid_constant__ CUtensorMap tmQ1, const K1Params P) {
    extern __shared__ __align__(1024) uint8_t smem[];
    const uint32_t sb = smem_u32(smem);
    const int tid = threadIdx.x, warp = __shfl_sync(0xffffffffu, tid >> 5, 0), lane = tid & 31;
    const int mi = blockIdx.x >> 3, nj = blockIdx.x & 7;
    const int u0 = (int)((0x1bbd22e51c80ull >> (5 * nj)) & 31), u1 = (int)((0x1bbd22e51c80ull >> (5 * nj + 5)) & 31);
    const uint32_t bar_full = sb + K1_BAR, bar_side = bar_full + 32, bar_kg = bar_full + 40;
    uint32_t* stage_cnt = (uint32_t*)(smem + K1_BAR + 64);
    if (tid == 0) { TSTAMP(0, 0); CSTAMP(0, 14); }
    pdl_launch();
    auto load_stage = [&](int kb) {
        const int s = kb % K1_STAGES;
        const uint32_t st = sb + s * K1_STAGE;
        mbar_expect_tx(bar_full + 8 * s, K1_STAGE);
        tma_load_2d(st, &tmX, kb * 64, mi * 128, bar_full + 8 * s);
#pragma unroll 1
        for (int q = 0; q < 4; q++) tma_load_2d(st + 16384 + q * 8192, &tmW, (u0 + q) * 64, kb * 64, bar_full + 8 * s);
    };
    if (tid == 0) {
        if (sb & 1023) __trap();
        for (int s = 0; s < K1_STAGES; s++) { mbar_init(bar_full + 8 * s, 1); stage_cnt[s] = 0; }
        mbar_init(bar_side, 1);
        mbar_init(bar_kg, 1);
        mbar_init_fence();
        fence_async();
        load_stage(0);
        load_stage(1);
        mbar_expect_tx(bar_kg, 6 * 1024);
        {
            const int o = blockIdx.x * 512;
            bulk_g2s(sb + K1_RAW, P.a_re + o, 1024, bar_kg); bulk_g2s(sb + K1_RAW + 1024, P.a_im + o, 1024, bar_kg);
            bulk_g2s(sb + K1_RAW + 2048, P.b_re + o, 1024, bar_kg); bulk_g2s(sb + K1_RAW + 3072, P.b_im + o, 1024, bar_kg);
            bulk_g2s(sb + K1_RAW + 4096, P.c_re + o, 1024, bar_kg); bulk_g2s(sb + K1_RAW + 5120, P.c_im + o, 1024, bar_kg);
        }
        const bool has_wo = blockIdx.x < 72;
        mbar_expect_tx(bar_side, 128 * 144 + 144 + (has_wo ? 8 * 1152 : 0));
        tma_load_2d(sb + K1_XS, &tmXs, nj * 72, mi * 128, bar_side);
        bulk_g2s(sb + K1_GW, P.gate_w + nj * 72, 144, bar_side);
        if (has_wo) {
#pragma unroll 1
            for (int r = 0; r < 8; r++) {
                const int hg = blockIdx.x / 9, ch = blockIdx.x - 9 * hg;
                const int row = ch < 8 ? (4 * hg + (ch >> 1)) * DH + 8 * (ch & 1) + r : (4 * hg + (r >> 1)) * DH + 16 + (r & 1);
                bulk_g2s(sb + K1_WO + r * 1168, P.wo + row * DM, 1152, bar_side);
            }
        }
        load_stage(2);
    }
    __syncthreads();

    if (warp < 8) {
        const int wg = warp >> 2, wi = warp & 3, g = lane >> 2, c = lane & 3;
        float acc[128];
#pragma unroll
        for (int i = 0; i < 128; i++) acc[i] = 0.f;
        fence_regs(acc);
#pragma unroll
        for (int kb = 0; kb < 9; kb++) {
            const int s = kb % K1_STAGES;
            mbar_wait_warp(bar_full + 8 * s, (kb / K1_STAGES) & 1);
            if (kb == 0 && tid == 0) TSTAMP(0, 1);
            const uint32_t st = sb + s * K1_STAGE;
            const uint64_t da = mkdesc(st + wg * 8192, 16, 1024, 1);
            const uint64_t db = mkdesc(st + 16384, 8192, 1024, 1);
            wg_fence();
#pragma unroll
            for (int kk = 0; kk < 4; kk++) wg_ss_n256_tb(acc, da + kk * 2, db + kk * 128, 1);
            wg_commit();
            if (kb > 0 && kb - 1 + K1_STAGES < 9) {
                wg_wait<1>();
                if ((tid & 127) == 0 && (atomicAdd(&stage_cnt[(kb - 1) % K1_STAGES], 1u) & 1u)) load_stage(kb - 1 + K1_STAGES);
            }
        }
        wg_wait<0>();
        fence_regs(acc);
        if (tid == 0) TSTAMP(0, 2);
        named_bar(5, 384);
        const float qscale = 0.23570226039551584f * 1.4426950408889634f;
        const int s_lo = (u0 * 64 + 17) / 18, s_hi = (u1 * 64) / 18;
        uint8_t* stg = smem + (8 * wg + 2 * wi) * 384 + g * 16 + (1 - s_lo) * 6144;
        const int nb_end = 8 * (u1 - u0);
#pragma unroll
        for (int n9 = 0; n9 < 9; n9++) {
            const int col = u0 * 64 + 8 * n9 + 2 * c;
            const int slot = (col * 3641) >> 16, dim = col - 18 * slot;
            uint8_t* ps = stg + slot * 6144 + ((dim & 24) << 4) + ((dim & 7) << 1);
#pragma unroll
            for (int rep = 0; rep < 4; rep++) {
                const int nb = n9 + 9 * rep;
                if (nb < 32 && (nb < 24 || nb < nb_end)) {
                    const float sc = slot + 4 * rep < 32 ? qscale : 1.f;
                    *(uint32_t*)(ps + rep * 4 * 6144) = pack_bf16(acc[4 * nb] * sc, acc[4 * nb + 1] * sc);
                    *(uint32_t*)(ps + rep * 4 * 6144 + 384) = pack_bf16(acc[4 * nb + 2] * sc, acc[4 * nb + 3] * sc);
                }
            }
        }
        if (tid == 0) TSTAMP(0, 8);
        {
            const int r = wg * 64 + (tid & 63), blk = r >> 3;
            const uint32_t k0 = is_mufu(blk, 0) ? 0u : 0x42FE4380u, k1 = is_mufu(blk, 1) ? 0u : 0x42FE4380u;
            const int p_lo = (u0 * 64 + 1) / 18, p_hi = (u1 * 64 + 1) / 18;
            uint8_t* ps = smem + blk * 384 + 256 + (r & 7) * 16 + (1 - s_lo) * 6144;
#pragma unroll 1
            for (int sl = p_lo + ((tid >> 6) & 1); sl < p_hi; sl += 2) {
                const int part = sl >> 5;
                *(uint32_t*)(ps + sl * 6144 + 4) = part == 1 ? k0 : (part == 2 ? 0x00003F80u : 0u);
                *(uint2*)(ps + sl * 6144 + 8) = make_uint2(part == 1 ? k1 : 0u, 0u);
            }
        }
        fence_async();
        named_bar(1, 256);
        if (tid == 0) {
            int sl = s_lo;
            const int n = s_hi - s_lo;
            auto st = [&](const CUtensorMap* tm, int cnt) {
                asm volatile("cp.async.bulk.tensor.3d.global.shared::cta.bulk_group [%0, {%2, %3, %4}], [%1];"
                             ::"l"(tm), "r"(sb + (sl - s_lo + 1) * 6144), "r"(0), "r"(mi * 48), "r"(sl) : "memory");
                sl += cnt;
            };
            if (n & 8) st(&tmQ8, 8);
            if (n & 4) st(&tmQ4, 4);
            if (n & 2) st(&tmQ2, 2);
            if (n & 1) st(&tmQ1, 1);
            bulk_commit();
        }
        if (tid == 0) TSTAMP(0, 12);
        {
            const int tw = tid & 127, right = tw >> 6, r = tw & 63;
            const int e = 18 - (18 * s_lo - 64 * u0), d_hi = 64 * u1 - 18 * s_hi;
            const int sl = right ? s_hi : s_lo - 1, o = wg * 3072 + (r >> 3) * 384 + (r & 7) * 16;
            uint8_t* gp = g_qkv + (size_t)sl * SLOT_BYTES + mi * 6144 + o;
            const uint8_t* sp = smem + (sl - s_lo + 1) * 6144 + o;
#pragma unroll
            for (int ch = 0; ch < 3; ch++) {
                const bool own = right ? 8 * ch + 8 <= d_hi : (e < 18 && 8 * ch >= e);
                if (own) *(uint4*)(gp + ch * 128) = *(const uint4*)(sp + ch * 128);
            }
            const int edge = right ? d_hi : e, ch = edge >> 3;
            const int w_lo = right ? 0 : (edge & 7) >> 1, w_hi = (edge & 7) == 0 || (!right && e == 18) ? 0 : (right ? (edge & 7) >> 1 : 4);
#pragma unroll 1
            for (int wd = w_lo; wd < w_hi; wd++) *(uint32_t*)(gp + ch * 128 + 4 * wd) = *(const uint32_t*)(sp + ch * 128 + 4 * wd);
        }
        {
            const int e = 18 - (18 * s_lo - 64 * u0), d_hi = 64 * u1 - 18 * s_hi;
            const int k_lo = max(32, e < 18 ? s_lo - 1 : s_lo), k_hi = min(64, d_hi > 0 ? s_hi + 1 : s_hi);
            const int r = tid & 127;
            const uint8_t* pr = smem + (1 - s_lo) * 6144 + (r >> 3) * 384 + (r & 7) * 16;
#pragma unroll 4
            for (int sl = k_lo + wg; sl < k_hi; sl += 2) {
                const uint8_t* p = pr + sl * 6144;
                uint4 v0 = *(const uint4*)p, v1 = *(const uint4*)(p + 128);
                uint32_t v2 = *(const uint32_t*)(p + 256);
                if (sl < s_lo || sl >= s_hi) {
                    const int w_lo = sl < s_lo ? e >> 1 : 0, w_hi = sl >= s_hi ? d_hi >> 1 : 9;
                    v0.x = (0 >= w_lo && 0 < w_hi) ? v0.x : 0u; v0.y = (1 >= w_lo && 1 < w_hi) ? v0.y : 0u;
                    v0.z = (2 >= w_lo && 2 < w_hi) ? v0.z : 0u; v0.w = (3 >= w_lo && 3 < w_hi) ? v0.w : 0u;
                    v1.x = (4 >= w_lo && 4 < w_hi) ? v1.x : 0u; v1.y = (5 >= w_lo && 5 < w_hi) ? v1.y : 0u;
                    v1.z = (6 >= w_lo && 6 < w_hi) ? v1.z : 0u; v1.w = (7 >= w_lo && 7 < w_hi) ? v1.w : 0u;
                    v2 = 8 < w_hi ? v2 : 0u;
                }
                uint32_t a = hfma_bf(v0.x, v0.x, 0u), b = hfma_bf(v0.y, v0.y, 0u), c2 = hfma_bf(v0.z, v0.z, 0u);
                a = hfma_bf(v0.w, v0.w, a); b = hfma_bf(v1.x, v1.x, b); c2 = hfma_bf(v1.y, v1.y, c2);
                a = hfma_bf(v1.z, v1.z, a); b = hfma_bf(v1.w, v1.w, b); c2 = hfma_bf(v2, v2, c2);
                const float n2 = (bf_lo(a) + bf_hi(a)) + (bf_lo(b) + bf_hi(b)) + (bf_lo(c2) + bf_hi(c2));
                const uint32_t mx = __reduce_max_sync(0xffffffffu, __float_as_uint(n2));
                if (lane == 0) g_kn[(sl < s_lo ? 2048 : 0) + (sl - 32) * 64 + mi * 4 + wi] = __uint_as_float(mx);
            }
        }
        if (tid == 0) TSTAMP(0, 3);
        {
            const int t = tid & 127;
            float D[1][5][4];
            const float k0[1] = {((const float*)(smem + K1_K0))[(2 + wg) * 4 + wi]};
            kgen_product<1>((const float4*)(smem + K1_PAR) + (2 + wg) * 256, D, t);
            uint8_t* kw = smem + K1_KW + (2 + wg) * 11616;
            kgen_sum<1>(D, k0, (float*)kw, g_Fb + (4 * blockIdx.x + 2 + wg) * FB_BYTES, 0, 2 + wg, t);
        }
        if (tid == 0) asm volatile("cp.async.bulk.wait_group.read 0;" ::: "memory");
        if (tid == 0) { TSTAMP(0, 4); CSTAMP(0, 15); }
    } else {
        const int t = tid & 127, w = t >> 5, g = lane >> 2;
        const float dt_l = bf16r(expf(__bfloat162float(P.log_dt[4 * blockIdx.x + (lane & 3)])));
        mbar_wait_warp(bar_side, 0);
        if (blockIdx.x < 72) {
#pragma unroll 1
            for (int pl = t; pl < 576; pl += 128) {
                const int q = pl >> 3, r = pl & 7, jj = (q * 7282) >> 16, nb = q - jj * 9;
                *(uint4*)(g_woT + jj * WOT_BYTES + blockIdx.x * 1152 + nb * 128 + r * 16) = *(const uint4*)(smem + K1_WO + r * 1168 + q * 16);
            }
        }
        float sum = 0.f, sum2 = 0.f;
#pragma unroll 3
        for (int k = 0; k < 9; k++) {
            const uint4 xv = *(const uint4*)(smem + K1_XS + t * 144 + k * 16), wv = *(const uint4*)(smem + K1_GW + k * 16);
            const uint32_t xa[4] = {xv.x, xv.y, xv.z, xv.w}, wa[4] = {wv.x, wv.y, wv.z, wv.w};
#pragma unroll
            for (int e = 0; e < 4; e++) {
                uint32_t pr;
                asm("mul.rn.bf16x2 %0, %1, %2;" : "=r"(pr) : "r"(xa[e]), "r"(wa[e]));
                sum += bf_lo(pr); sum2 += bf_hi(pr);
            }
        }
        g_gatep[nj * SEQ + mi * 128 + t] = sum + sum2;
        const int m = lane >> 3, rr = lane & 7;
        uint32_t addr = sb + K1_XS + (8 * (4 * w + m) + rr) * 144;
        uint32_t daddr = sb + K1_US + rr * 272 + (m & 1) * 128 + (2 * w + (m >> 1)) * 16;
#pragma unroll 3
        for (int cb = 0; cb < 9; cb++, addr += 16, daddr += 8 * 272) {
            uint32_t r0, r1, r2, r3;
            asm volatile("ldmatrix.sync.aligned.m8n8.x4.trans.shared.b16 {%0,%1,%2,%3}, [%4];"
                         : "=r"(r0), "=r"(r1), "=r"(r2), "=r"(r3) : "r"(addr));
            asm volatile("stmatrix.sync.aligned.m8n8.x4.shared.b16 [%0], {%1,%2,%3,%4};"
                         ::"r"(daddr), "r"(r0), "r"(r1), "r"(r2), "r"(r3) : "memory");
        }
        named_bar(4, 128);
#pragma unroll 3
        for (int p = t; p < 72 * 16; p += 128) {
            const int ch = p >> 4, kc = (p >> 3) & 1, a = p & 7;
            *(uint4*)(g_U + (size_t)(nj * 72 + ch) * 4096 + kc * 2048 + (8 * mi + a) * 16) = *(const uint4*)(smem + K1_US + ch * 272 + (p & 15) * 16);
        }
        (void)g;
        if (t == 0) TSTAMP(0, 5);
        mbar_wait_warp(bar_kg, 0);
#pragma unroll 1
        for (int k = 0; k < 4; k++) {
            const float k0 = kgen_params((const uint16_t*)(smem + K1_RAW) + k * 128, 512, (float4*)(smem + K1_PAR) + k * 256,
                                         __shfl_sync(0xffffffffu, dt_l, k), t);
            if (lane == 0) ((float*)(smem + K1_K0))[k * 4 + w] = k0;
        }
        if (t == 0) TSTAMP(0, 7);
        named_bar(5, 384);
        {
            float D[2][5][4];
            const float k0[2] = {((const float*)(smem + K1_K0))[w], ((const float*)(smem + K1_K0))[4 + w]};
            kgen_product<2>((const float4*)(smem + K1_PAR), D, t);
            uint8_t* kw = smem + K1_KW;
            kgen_sum<2>(D, k0, (float*)kw, g_Fb + (4 * blockIdx.x) * FB_BYTES, FB_BYTES, 4, t);
        }
        if (t == 0) TSTAMP(0, 6);
    }
}

constexpr int OP_A = 0;
constexpr int OP_B = 8 * 18432;
constexpr int OP_END = OP_B + WOT_BYTES;
constexpr int OP_BT = 0;
constexpr int OP_OUT = 2 * 18432;
__device__ __forceinline__ void op_init_barriers(uint32_t bar) {
    for (int s = 0; s < 9; s++) mbar_init(bar + 8 * s, 1);
    mbar_init(bar + 72, 2);
    mbar_init(bar + 80, 1);
}
__device__ __forceinline__ void op_load_wo(uint32_t sb, uint32_t bar, int nj) {
    mbar_expect_tx(bar + 64, WOT_BYTES);
    for (int q = 0; q < 3; q++) bulk_g2s(sb + OP_B + q * 27648, g_woT + nj * WOT_BYTES + q * 27648, 27648, bar + 64);
}
__device__ __forceinline__ void op_load_rest(uint32_t sb, uint32_t bar, const CUtensorMap* tmB, int mi, int nj) {
#pragma unroll 1
    for (int hg = 0; hg < 8; hg++) {
        mbar_expect_tx(bar + 8 * hg, 18432);
        bulk_g2s(sb + OP_A + hg * 18432, g_O + (size_t)(hg * 256 + mi * 16) * 1152, 18432, bar + 8 * hg);
    }
    mbar_wait(bar + 72, 0);
    mbar_expect_tx(bar + 80, 144 * 128);
    tma_load_2d(sb + OP_BT, tmB, mi * 64, nj * 144, bar + 80);
}
__device__ __forceinline__ void op_consumer(uint8_t* smem, uint32_t sb, uint32_t bar, const CUtensorMap* tmOut, int mi, int nj, int wg,
                                            int tw) {
    const int wi = tw >> 5, lane = tw & 31, g = lane >> 2, c = lane & 3;
    const int r0 = wg * 64 + wi * 16 + g;
    float g0 = 0.f, g1 = 0.f;
#pragma unroll
    for (int j = 0; j < 8; j++) { g0 += g_gatep[j * SEQ + mi * 128 + r0]; g1 += g_gatep[j * SEQ + mi * 128 + r0 + 8]; }
    g0 = bf16r(1.f / (1.f + expf(-bf16r(g0))));
    g1 = bf16r(1.f / (1.f + expf(-bf16r(g1))));
    float acc[36];
#pragma unroll
    for (int i = 0; i < 36; i++) acc[i] = 0.f;
    fence_regs(acc);
    mbar_wait_warp(bar + 64, 0);
#pragma unroll
    for (int hg = 0; hg < 8; hg++) {
        mbar_wait_warp(bar + 8 * hg, 0);
        if (hg == 0 && wg == 0 && tw == 0) TSTAMP(2, 1);
        wg_fence();
#pragma unroll
        for (int st = (9 * hg) / 2; st < (9 * hg + 9) / 2; st++) {
            const int q0 = 2 * st, q1 = q0 + 1;
            const int a0 = (q0 / 9) * 18432 + (q0 % 9) * 128, a1 = (q1 / 9) * 18432 + (q1 % 9) * 128;
            wg_ss_n72_tb(acc, mkdesc(sb + OP_A + wg * 8 * 1152 + a0, a1 - a0, 1152, 0), mkdesc(sb + OP_B + st * 2304, 1152, 128, 0), 1);
        }
        wg_commit();
        if (hg == 2) {
            wg_wait<1>();
            if (tw == 0) mbar_arrive(bar + 72);
        }
    }
    wg_wait<0>();
    fence_regs(acc);
    if (wg == 0 && tw == 0) TSTAMP(2, 2);
    named_bar(1, 256);
    mbar_wait_warp(bar + 80, 0);
    if (wg == 0 && tw == 0) TSTAMP(2, 3);
    const uint32_t g0p = pack_bf16(g0, g0), g1p = pack_bf16(g1, g1), h0p = pack_bf16(1.f - g0, 1.f - g0), h1p = pack_bf16(1.f - g1, 1.f - g1);
    uint8_t* stg = smem + OP_OUT + wg * 18432 + (wi * 16 + g) * 144 + 4 * c;
#pragma unroll
    for (int nb = 0; nb < 9; nb++) {
        uint32_t b0, b1;
        const int row = 2 * (8 * nb + (lane & 7)) + ((lane >> 3) & 1), chunk = 4 * wg + wi;
        const uint32_t addr = sb + OP_BT + row * 128 + ((chunk ^ (row & 7)) << 4);
        asm volatile("ldmatrix.sync.aligned.m8n8.x2.trans.shared.b16 {%0,%1}, [%2];" : "=r"(b0), "=r"(b1) : "r"(addr));
        *(uint32_t*)(stg + 16 * nb) = hadd_bf(hmul_bf(g0p, pack_bf16(acc[4 * nb], acc[4 * nb + 1])), hmul_bf(h0p, b0));
        *(uint32_t*)(stg + 8 * 144 + 16 * nb) = hadd_bf(hmul_bf(g1p, pack_bf16(acc[4 * nb + 2], acc[4 * nb + 3])), hmul_bf(h1p, b1));
    }
    fence_async();
    named_bar(2 + wg, 128);
    if (tw == 0) {
        asm volatile("cp.async.bulk.tensor.2d.global.shared::cta.bulk_group [%0, {%2, %3}], [%1];"
                     ::"l"(tmOut), "r"(sb + OP_OUT + wg * 18432), "r"(nj * 72), "r"(mi * 128 + wg * 64) : "memory");
        bulk_commit();
        asm volatile("cp.async.bulk.wait_group.read 0;" ::: "memory");
    }
    if (wg == 0 && tw == 0) TSTAMP(2, 4);
}

constexpr int K2_THREADS = 512;
constexpr int CV_BYTES = 17664;
constexpr int K2_K = 0, K2_V = SLOT_BYTES, K2_CV = 2 * SLOT_BYTES, K2_BAR = K2_CV + 2 * CV_BYTES;
constexpr int K2_SMEM = K2_BAR + 512;
static_assert(K2_SMEM <= 232448, "");
constexpr int CV_PAD = 512, CV_CH = 2560;
constexpr int CV_U = 0, CV_R = 5120, CV_Y = 5120;

struct K2Params { const __nv_bfloat16 *a_re, *a_im, *b_re, *b_im, *c_re, *c_im, *log_dt, *dskip; };

constexpr int KG_PAR = CV_R;
constexpr int KG_FS = CV_R;
constexpr int KG_FB = KG_FS + 4 * 644 * 4;
static_assert(KG_FB + 1312 <= CV_BYTES && CV_R + R_WORDS * 4 <= KG_FB && CV_Y + 64 * 36 * 4 <= CV_BYTES, "");

__device__ __forceinline__ void conv_issue_loads(uint32_t buf, int d, uint32_t bar) {
    mbar_expect_tx(bar, 4096);
    bulk_g2s(buf + CV_U + CV_PAD, g_U + (size_t)d * 4096, 2048, bar);
    bulk_g2s(buf + CV_U + CV_CH + CV_PAD, g_U + (size_t)d * 4096 + 2048, 2048, bar);
}

__device__ __forceinline__ void conv_load_a(uint32_t (&a)[4][4], const uint32_t* R, int s0) {
#pragma unroll
    for (int r = 0; r < 4; r++) {
        const volatile uint32_t* p = R + 16 * (s0 + 8 * (r >> 1) + (r & 1));
        a[r][0] = p[0]; a[r][1] = p[8]; a[r][2] = p[-8]; a[r][3] = p[0];
        fence_regs(a[r]);
    }
}
template <int Q>
__device__ __forceinline__ void conv_issue(float (&acc)[4][16], const uint32_t (&a)[4][4], uint32_t du, int s0) {
    const uint32_t db = du - s0;
    wg_fence();
#pragma unroll
    for (int r = 0; r < 4; r++) {
#pragma unroll
        for (int q = Q; q < 4; q++)
            wg_conv_n32(acc[q], a[r][0], a[r][1], a[r][2], a[r][3], db + 32 * q - (8 * (r >> 1) + (r & 1)));
    }
    wg_commit();
}
template <int Q>
__device__ __forceinline__ void conv_phase(float (&acc)[4][16], const uint32_t* R, uint32_t du) {
#pragma unroll 1
    for (int s0 = 32 * Q; s0 < 32 * Q + 32; s0 += 16) {
        uint32_t a[4][4];
        conv_load_a(a, R, s0);
        conv_issue<Q>(acc, a, du, s0);
        wg_wait<0>();
    }
}

__device__ __forceinline__ void conv_mma(float (&acc)[4][16], uint8_t* smem, uint32_t sb, uint32_t buf, uint32_t bar, uint32_t parity,
                                         int wg, int tw) {
    const int h = tw >> 5, lane = tw & 31, g = lane >> 2, c = lane & 3;
    if (tw < 64) *(uint4*)(smem + buf + CV_U + (tw >> 5) * CV_CH + (tw & 31) * 16) = make_uint4(0, 0, 0, 0);
    fence_async();
    named_bar(4 + wg, 128);
    if (tw == 0 && wg == 0) TSTAMP(1, 11);
#pragma unroll
    for (int q = 0; q < 4; q++)
#pragma unroll
        for (int i = 0; i < 16; i++) acc[q][i] = 0.f;
#pragma unroll
    for (int q = 0; q < 4; q++) fence_regs(acc[q]);
    const uint32_t* R = (const uint32_t*)(smem + buf + CV_R) + 16 + 32 * h + g - 2 * c;
    const uint32_t du = (uint32_t)mkdesc(sb + buf + CV_U + CV_PAD, CV_CH, 128, 0);
    mbar_wait_warp(bar, parity);
    if (tw == 0 && wg == 0) TSTAMP(1, 12);
    conv_phase<0>(acc, R, du); conv_phase<1>(acc, R, du); conv_phase<2>(acc, R, du); conv_phase<3>(acc, R, du);
#pragma unroll
    for (int q = 0; q < 4; q++) fence_regs(acc[q]);
    if (tw == 0 && wg == 0) TSTAMP(1, 13);
}
__device__ __forceinline__ void conv_finish(float (&acc)[4][16], uint8_t* smem, uint32_t sb, uint32_t buf, int d, __nv_bfloat16 dskip,
                                            int wg, int tw) {
    const int h = tw >> 5, lane = tw & 31, g = lane >> 2, c = lane & 3;
    uint32_t* Y = (uint32_t*)(smem + buf + CV_Y);
    const uint32_t ds2 = (uint32_t)__bfloat16_as_ushort(dskip) * 0x10001u;
    uint32_t carry0 = 0u, carry1 = 0u;
#pragma unroll
    for (int rd = 0; rd < 2; rd++) {
        named_bar(4 + wg, 128);
        uint32_t* Yw = Y + (h * 16 + g) * 36 + c;
        Yw[0] = carry0; Yw[8 * 36] = carry1;
#pragma unroll
        for (int nb = 0; nb < 8; nb++) {
            const float* A = &acc[2 * rd + (nb >> 2)][4 * (nb & 3)];
            carry0 = pack_bf16(A[0], A[1]); carry1 = pack_bf16(A[2], A[3]);
            Yw[4 + 4 * nb] = carry0;
            Yw[8 * 36 + 4 + 4 * nb] = carry1;
        }
        named_bar(4 + wg, 128);
        const int P = tw & 31, bq = tw >> 5;
        uint32_t yw[4];
#pragma unroll
        for (int b = 0; b < 4; b++) {
            const uint32_t* p = Y + (4 * bq + b) * 36 + 4 + P;
            const uint32_t w0 = p[0], w1 = p[16 * 36 - 1], w2 = p[32 * 36 - 2], w3 = p[48 * 36 - 3];
            yw[b] = pack_bf16((bf_lo(w0) + bf_lo(w1)) + (bf_lo(w2) + bf_lo(w3)), (bf_hi(w0) + bf_hi(w1)) + (bf_hi(w2) + bf_hi(w3)));
        }
        uint2* up = (uint2*)(smem + buf + CV_U + (bq >> 1) * CV_CH + CV_PAD + (64 * rd + 2 * P) * 16 + (bq & 1) * 8);
#pragma unroll
        for (int e2 = 0; e2 < 2; e2++) {
            const uint2 u0 = up[2 * e2];
            const uint32_t sel = e2 ? 0x7632 : 0x5410;
            up[2 * e2] = make_uint2(hadd_bf(prmt(yw[0], yw[1], sel), hmul_bf(u0.x, ds2)), hadd_bf(prmt(yw[2], yw[3], sel), hmul_bf(u0.y, ds2)));
        }
    }
    fence_async();
    named_bar(4 + wg, 128);
    if (tw == 0) {
        bulk_s2g((uint8_t*)g_bT + (size_t)d * 4096, sb + buf + CV_U + CV_PAD, 2048);
        bulk_s2g((uint8_t*)g_bT + (size_t)d * 4096 + 2048, sb + buf + CV_U + CV_CH + CV_PAD, 2048);
        bulk_commit();
        asm volatile("cp.async.bulk.wait_group.read 0;" ::: "memory");
    }
}

template <int BN> __device__ __forceinline__ void qk_tile(float (&s)[BN / 2], const uint32_t (&q)[8], uint64_t dk0, uint64_t dk1) {
    if constexpr (BN == 64) { wg_qk_n64_first(s, q[0], q[1], q[2], q[3], dk0); wg_qk_n64_acc(s, q[4], q[5], q[6], q[7], dk1); }
    if constexpr (BN == 96) { wg_qk_n96_first(s, q[0], q[1], q[2], q[3], dk0); wg_qk_n96_acc(s, q[4], q[5], q[6], q[7], dk1); }
    if constexpr (BN == 128) { wg_qk_n128_first(s, q[0], q[1], q[2], q[3], dk0); wg_qk_n128_acc(s, q[4], q[5], q[6], q[7], dk1); }
}
template <int BN> __device__ __forceinline__ void exp_pv(float (&s)[BN / 2], float (&o)[12], uint64_t dv) {
#pragma unroll
    for (int kk = 0; kk < BN / 16; kk++) {
        uint32_t p[4];
#pragma unroll
        for (int i = 0; i < 4; i++) {
            const float x0 = s[8 * kk + 2 * i], x1 = s[8 * kk + 2 * i + 1];
            p[i] = is_mufu(2 * kk + (i >> 1), i & 1) ? exp2_mufu(x0, x1) : exp2_poly(x0, x1);
        }
        fence_regs(p);
        wg_fence();
        wg_pv_n24(o, p[0], p[1], p[2], p[3], dv + kk * 48);
    }
}

constexpr int TILE_DESC64 = 8 * 384 / 16;

__device__ __forceinline__ void attn_fast(float (&o)[12], const uint32_t (&q)[8], uint64_t dk0, uint64_t dk1, uint64_t dv,
                                          uint32_t bar_kv) {
    float s[64];
#pragma unroll 1
    for (int j = 0; j < 16; j++) {
        if ((j & 1) == 0) mbar_wait_warp(bar_kv + 8 * (j >> 1), 0);
        wg_fence();
        qk_tile<128>(s, q, dk0 + j * (2 * TILE_DESC64), dk1 + j * (2 * TILE_DESC64));
        wg_commit();
        wg_wait<0>();
        fence_regs(s);
        exp_pv<128>(s, o, dv + j * (2 * TILE_DESC64));
        wg_commit();
        wg_wait<0>();
    }
}

__device__ __forceinline__ void attn_slow(float (&o)[12], const uint32_t (&qin)[8], uint64_t dk0, uint64_t dk1, uint64_t dv,
                                       uint32_t bar_kv, int c) {
    uint32_t q[8];
#pragma unroll
    for (int i = 0; i < 8; i++) q[i] = qin[i];
    q[4] = c == 0 ? qin[4] : 0u;
    q[5] = c == 0 ? qin[5] : 0u;
    fence_regs(q);
    float m0 = -INFINITY, m1 = -INFINITY;
    float s[32];
#pragma unroll 1
    for (int j = 0; j < 32; j++) {
        if ((j & 3) == 0) mbar_wait_warp(bar_kv + 8 * (j >> 2), 0);
        wg_fence();
        qk_tile<64>(s, q, dk0 + j * TILE_DESC64, dk1 + j * TILE_DESC64);
        wg_commit();
        wg_wait<0>();
        fence_regs(s);
        fence_regs(o);
        float t0 = m0, t1 = m1;
#pragma unroll
        for (int nb = 0; nb < 8; nb++) {
            t0 = fmaxf(t0, fmaxf(s[4 * nb], s[4 * nb + 1]));
            t1 = fmaxf(t1, fmaxf(s[4 * nb + 2], s[4 * nb + 3]));
        }
        t0 = fmaxf(t0, __shfl_xor_sync(0xffffffffu, t0, 1)); t0 = fmaxf(t0, __shfl_xor_sync(0xffffffffu, t0, 2));
        t1 = fmaxf(t1, __shfl_xor_sync(0xffffffffu, t1, 1)); t1 = fmaxf(t1, __shfl_xor_sync(0xffffffffu, t1, 2));
        const float r0 = ex2f(m0 - t0), r1 = ex2f(m1 - t1);
        m0 = t0; m1 = t1;
#pragma unroll
        for (int nb = 0; nb < 3; nb++) { o[4 * nb] *= r0; o[4 * nb + 1] *= r0; o[4 * nb + 2] *= r1; o[4 * nb + 3] *= r1; }
        uint32_t p[16];
#pragma unroll
        for (int nb = 0; nb < 8; nb++) {
            p[2 * nb] = pack_bf16(ex2f(s[4 * nb] - m0), ex2f(s[4 * nb + 1] - m0));
            p[2 * nb + 1] = pack_bf16(ex2f(s[4 * nb + 2] - m1), ex2f(s[4 * nb + 3] - m1));
        }
        fence_regs(p);
        fence_regs(o);
        wg_fence();
#pragma unroll
        for (int kk = 0; kk < 4; kk++) wg_pv_n24(o, p[4 * kk], p[4 * kk + 1], p[4 * kk + 2], p[4 * kk + 3], dv + j * TILE_DESC64 + kk * 48);
        wg_commit();
        wg_wait<0>();
        fence_regs(o);
    }
}

__global__ void __launch_bounds__(K2_THREADS, 1)
k2_attn(const K2Params P) {
    extern __shared__ __align__(1024) uint8_t smem[];
    const uint32_t sb = smem_u32(smem);
    const int tid = threadIdx.x, wg = uniform_wg(), tw = tid & 127;
    const uint32_t bar_kv = sb + K2_BAR, bar_cv = bar_kv + 64, bar_p = bar_cv + 32;
    float* red = (float*)(smem + K2_BAR + 192);
    if (tid == 0) {
        for (int i = 0; i < 8; i++) mbar_init(bar_kv + 8 * i, 1);
        for (int i = 0; i < 4; i++) { mbar_init(bar_cv + 8 * i, 1); mbar_init(bar_p + 8 * i, 1); }
        mbar_init_fence();
    }
    __syncthreads();
    if (tid == 0) TSTAMP(1, 0);
    const int wi = tw >> 5, lane = tw & 31, g = lane >> 2, c = lane & 3;

    if (blockIdx.x < 4) {
        const int d_first = 512 + blockIdx.x * 16 + wg;
        const uint32_t cbuf = wg * CV_BYTES;
        uint8_t* fbs = smem + K2_V + wg * 4 * 1312;
        uint8_t* raw = smem + K2_V + 24576 + wg * 4 * 1536;
        if (tw == 0) {
            mbar_expect_tx(bar_p + 8 * wg, 4 * 1536);
#pragma unroll 1
            for (int r = 0; r < 4; r++) {
                const int o = (d_first + 4 * r) * 128;
                const uint32_t dst = smem_u32(raw) + r * 1536;
                bulk_g2s(dst, P.a_re + o, 256, bar_p + 8 * wg); bulk_g2s(dst + 256, P.a_im + o, 256, bar_p + 8 * wg);
                bulk_g2s(dst + 512, P.b_re + o, 256, bar_p + 8 * wg); bulk_g2s(dst + 768, P.b_im + o, 256, bar_p + 8 * wg);
                bulk_g2s(dst + 1024, P.c_re + o, 256, bar_p + 8 * wg); bulk_g2s(dst + 1280, P.c_im + o, 256, bar_p + 8 * wg);
            }
        }
        const float dt_l = bf16r(expf(__bfloat162float(P.log_dt[d_first + 4 * (lane & 3)])));
        mbar_wait_warp(bar_p + 8 * wg, 0);
#pragma unroll 1
        for (int r = 0; r < 4; r++) {
            float D[1][5][4];
            const float k0[1] = {kgen_params((const uint16_t*)(raw + r * 1536), 128, (float4*)(smem + cbuf + KG_PAR),
                                             __shfl_sync(0xffffffffu, dt_l, r), tw)};
            __syncwarp();
            kgen_product<1>((const float4*)(smem + cbuf + KG_PAR), D, tw);
            named_bar(4 + wg, 128);
            kgen_sum<1>(D, k0, (float*)(smem + cbuf + KG_FS), fbs + r * 1312, 0, 4 + wg, tw);
            named_bar(4 + wg, 128);
        }
        pdl_wait();
#pragma unroll 1
        for (int r = 0; r < 4; r++) {
            const int d = d_first + 4 * r;
            if (r > 0) named_bar(4 + wg, 128);
            if (tw == 0) { fence_async(); conv_issue_loads(sb + cbuf, d, bar_cv + 8 * wg); }
            const __nv_bfloat16 dsk = P.dskip[d];
            kgen_expand(fbs + r * 1312, smem + cbuf + CV_R, tw);
            float acc[4][16];
            conv_mma(acc, smem, sb, cbuf, bar_cv + 8 * wg, r & 1, wg, tw);
            conv_finish(acc, smem, sb, cbuf, d, dsk, wg, tw);
        }
        if (tid == 0) TSTAMP(1, 1);
        return;
    }

    const int bid = blockIdx.x - 4, head = bid >> 2, quarter = bid & 3;
    const uint32_t cbuf = K2_CV + (wg & 1) * CV_BYTES;
    pdl_wait();
    pdl_launch();
    if (tid == 0) TSTAMP(1, 15);
    auto ssm_loads = [&](int w) {
        mbar_expect_tx(bar_p + 8 * w, FB_BYTES);
        bulk_g2s(sb + cbuf + KG_FB, g_Fb + (4 * bid + w) * FB_BYTES, FB_BYTES, bar_p + 8 * w);
        conv_issue_loads(sb + cbuf, 4 * bid + w, bar_cv + 8 * w);
    };
    if (tw == 0 && wg < 2) ssm_loads(wg);
    auto kv_loads = [&](int c0, int c1) {
        const uint8_t* gK = g_qkv + (size_t)(32 + head) * SLOT_BYTES;
        const uint8_t* gV = g_qkv + (size_t)(64 + head) * SLOT_BYTES;
        for (int i = c0; i < c1; i++) {
            mbar_expect_tx(bar_kv + 8 * i, 2 * 12288);
            bulk_g2s(sb + K2_K + i * 12288, gK + i * 12288, 12288, bar_kv + 8 * i);
            bulk_g2s(sb + K2_V + i * 12288, gV + i * 12288, 12288, bar_kv + 8 * i);
        }
    };
    if (tid == 256) kv_loads(0, 1);
    const __nv_bfloat16 dsk0 = P.dskip[4 * bid + wg];
    __syncwarp();
#pragma unroll 1
    for (int task = 0; task < 2; task++) {
        if ((task == 0) == (wg < 2)) {
            mbar_wait_warp(bar_p + 8 * wg, 0);
            kgen_expand(smem + cbuf + KG_FB, smem + cbuf + CV_R, tw);
            float acc[4][16];
            conv_mma(acc, smem, sb, cbuf, bar_cv + 8 * wg, 0, wg, tw);
            conv_finish(acc, smem, sb, cbuf, 4 * bid + wg, dsk0, wg, tw);
            if (wg < 2 && tw == 0) { fence_async(); ssm_loads(wg + 2); }
            if (tw == 0 && (wg == 0 || wg == 3)) TSTAMP(1, wg == 0 ? 1 : 2);
            __syncwarp();
        } else {
            uint32_t qf[2][6];
#pragma unroll
            for (int item = 0; item < 2; item++) {
                const int row0 = (quarter * 8 + item * 4 + wg) * 64 + wi * 16 + g;
                const uint8_t* gq = g_qkv + (size_t)head * SLOT_BYTES + (row0 >> 3) * 384 + g * 16;
                qf[item][0] = *(const uint32_t*)(gq + 4 * c);
                qf[item][1] = *(const uint32_t*)(gq + 384 + 4 * c);
                qf[item][2] = *(const uint32_t*)(gq + 128 + 4 * c);
                qf[item][3] = *(const uint32_t*)(gq + 384 + 128 + 4 * c);
                qf[item][4] = *(const uint32_t*)(gq + 256);
                qf[item][5] = *(const uint32_t*)(gq + 384 + 256);
            }

            float kmax2;
            {
                const float* kn = g_kn + head * 64;
                uint32_t m = __reduce_max_sync(0xffffffffu, max(__float_as_uint(kn[lane]), __float_as_uint(kn[32 + lane])));
                kmax2 = __uint_as_float(m);
                if (head == 3 || head == 17 || head == 28) {
                    m = __reduce_max_sync(0xffffffffu, max(__float_as_uint(kn[2048 + lane]), __float_as_uint(kn[2048 + 32 + lane])));
                    kmax2 += __uint_as_float(m);
                }
            }
#pragma unroll
            for (int item = 0; item < 2; item++) {
                float n0 = 0.f, n1 = 0.f;
#pragma unroll
                for (int i = 0; i < 6; i++) {
                    const uint32_t wv = (i >= 4 && c != 0) ? 0u : qf[item][i];
                    const float lo = bf_lo(wv), hi = bf_hi(wv);
                    if (i & 1) n1 = fmaf(lo, lo, fmaf(hi, hi, n1)); else n0 = fmaf(lo, lo, fmaf(hi, hi, n0));
                }
                n0 += __shfl_xor_sync(0xffffffffu, n0, 1); n0 += __shfl_xor_sync(0xffffffffu, n0, 2);
                n1 += __shfl_xor_sync(0xffffffffu, n1, 1); n1 += __shfl_xor_sync(0xffffffffu, n1, 2);
                const uint32_t qm = __reduce_max_sync(0xffffffffu, max(__float_as_uint(n0), __float_as_uint(n1)));
                if (lane == 0) red[16 + item * 16 + wg * 4 + wi] = __uint_as_float(qm);
                qf[item][4] = c == 0 ? qf[item][4] : (c == 1 ? 0x3F803F80u : 0u);
                qf[item][5] = c == 0 ? qf[item][5] : (c == 2 ? 0x3F803F80u : 0u);
            }
            if (tid == 256) kv_loads(1, 8);
            named_bar(4 + wg, 128);
            bool fast_item[2];
            {
#pragma unroll
                for (int item = 0; item < 2; item++) {
                    const uint32_t qm = __reduce_max_sync(0xffffffffu, __float_as_uint(red[16 + item * 16 + wg * 4 + (lane & 3)]));
                    fast_item[item] = __all_sync(0xffffffffu, __uint_as_float(qm) * kmax2 <= 3300.f);
                }
            }
            const uint64_t dk0 = mkdesc(sb + K2_K, 128, 384, 0);
            const uint64_t dk1 = mkdesc(sb + K2_K + 256, 0, 384, 0);
            const uint64_t dv = mkdesc(sb + K2_V, 384, 128, 0);
#pragma unroll 1
            for (int item = 0; item < 2; item++) {
                const int qt = quarter * 8 + item * 4 + wg;
                const int row0 = qt * 64 + wi * 16 + g;
                uint32_t q[8];
#pragma unroll
                for (int i = 0; i < 6; i++) q[i] = item ? qf[1][i] : qf[0][i];
                q[6] = 0u; q[7] = 0u;
                fence_regs(q);
                const bool fast = item ? fast_item[1] : fast_item[0];
                float o[12];
#pragma unroll
                for (int i = 0; i < 12; i++) o[i] = 0.f;
                fence_regs(o);
                if (tw == 0 && (wg == 0 || wg == 3)) TSTAMP(1, 3 + item * 2 + (wg == 3 ? 4 : 0));
                if (fast) attn_fast(o, q, dk0, dk1, dv, bar_kv);
                else attn_slow(o, q, dk0, dk1, dv, bar_kv, c);
                wg_wait<0>();
                fence_regs(o);
                if (tw == 0 && (wg == 0 || wg == 3)) TSTAMP(1, 4 + item * 2 + (wg == 3 ? 4 : 0));
                const float l0 = __shfl_sync(0xffffffffu, o[8], (lane & 28) | 1), l1 = __shfl_sync(0xffffffffu, o[10], (lane & 28) | 1);
                const float i0 = 1.f / l0, i1 = 1.f / l1;
                uint8_t* dst = g_O + (size_t)((head >> 2) * 256 + (row0 >> 3)) * 1152 + g * 16;
                uint8_t* dm = dst + (head & 3) * 256 + 4 * c;
                *(uint32_t*)(dm) = pack_bf16(o[0] * i0, o[1] * i0);
                *(uint32_t*)(dm + 1152) = pack_bf16(o[2] * i1, o[3] * i1);
                *(uint32_t*)(dm + 128) = pack_bf16(o[4] * i0, o[5] * i0);
                *(uint32_t*)(dm + 1152 + 128) = pack_bf16(o[6] * i1, o[7] * i1);
                if (c == 0) {
                    *(uint32_t*)(dst + 1024 + (head & 3) * 4) = pack_bf16(o[8] * i0, o[9] * i0);
                    *(uint32_t*)(dst + 1152 + 1024 + (head & 3) * 4) = pack_bf16(o[10] * i1, o[11] * i1);
                }
            }
        }
    }
}

constexpr int K3_THREADS = 288;
constexpr int K3_SMEM = OP_END + 128;
__global__ void __launch_bounds__(K3_THREADS, 1)
k3_out(const __grid_constant__ CUtensorMap tmB, const __grid_constant__ CUtensorMap tmOut) {
    extern __shared__ __align__(1024) uint8_t smem[];
    const uint32_t sb = smem_u32(smem), bar = sb + OP_END;
    const int tid = threadIdx.x, warp = __shfl_sync(0xffffffffu, tid >> 5, 0);
    const int mi = blockIdx.x >> 3, nj = blockIdx.x & 7;
    if (tid == 0) { TSTAMP(2, 0); op_init_barriers(bar); mbar_init_fence(); }
    __syncthreads();
    if (warp == 8) {
        if (tid == 256) {
            op_load_wo(sb, bar, nj);
            pdl_wait();
            op_load_rest(sb, bar, &tmB, mi, nj);
        }
    } else {
        op_consumer(smem, sb, bar, &tmOut, mi, nj, warp >> 2, tid & 127);
    }
}

typedef CUresult (*EncodeTiledFn)(CUtensorMap*, CUtensorMapDataType, cuuint32_t, void*, const cuuint64_t*, const cuuint64_t*,
                                  const cuuint32_t*, const cuuint32_t*, CUtensorMapInterleave, CUtensorMapSwizzle,
                                  CUtensorMapL2promotion, CUtensorMapFloatOOBfill);

void make_map(EncodeTiledFn fn, CUtensorMap* tm, const void* ptr, uint64_t cols, uint64_t rows, uint32_t box_c, uint32_t box_r,
              CUtensorMapSwizzle swz) {
    cuuint64_t dims[2] = {cols, rows};
    cuuint64_t strides[1] = {cols * 2};
    cuuint32_t box[2] = {box_c, box_r};
    cuuint32_t es[2] = {1, 1};
    fn(tm, CU_TENSOR_MAP_DATA_TYPE_BFLOAT16, 2, const_cast<void*>(ptr), dims, strides, box, es, CU_TENSOR_MAP_INTERLEAVE_NONE,
       swz, CU_TENSOR_MAP_L2_PROMOTION_L2_128B, CU_TENSOR_MAP_FLOAT_OOB_FILL_NONE);
}

void make_qkv_map(EncodeTiledFn fn, CUtensorMap* tm, void* ptr, uint32_t nslot) {
    cuuint64_t dims[3] = {64, 768, 96};
    cuuint64_t strides[2] = {128, (cuuint64_t)SLOT_BYTES};
    cuuint32_t box[3] = {64, 48, nslot};
    cuuint32_t es[3] = {1, 1, 1};
    fn(tm, CU_TENSOR_MAP_DATA_TYPE_BFLOAT16, 3, ptr, dims, strides, box, es, CU_TENSOR_MAP_INTERLEAVE_NONE,
       CU_TENSOR_MAP_SWIZZLE_NONE, CU_TENSOR_MAP_L2_PROMOTION_NONE, CU_TENSOR_MAP_FLOAT_OOB_FILL_NONE);
}

template <typename... KArgs, typename... Args>
void launch(void (*kern)(KArgs...), int grid, int block, int smem, cudaStream_t st, bool pdl, Args... args) {
    cudaLaunchConfig_t cfg = {};
    cfg.gridDim = dim3(grid); cfg.blockDim = dim3(block); cfg.dynamicSmemBytes = smem; cfg.stream = st;
    cudaLaunchAttribute at[1];
    at[0].id = cudaLaunchAttributeProgrammaticStreamSerialization;
    at[0].val.programmaticStreamSerializationAllowed = 1;
    cfg.attrs = at; cfg.numAttrs = pdl ? 1 : 0;
    cudaLaunchKernelEx(&cfg, kern, KArgs(args)...);
}

}

extern "C" void kernel_launch(void* const* d_in, const int* in_sizes, int n_in, void* d_out, int out_size) {
    (void)in_sizes; (void)n_in; (void)out_size;
    typedef const __nv_bfloat16* bp;
    static EncodeTiledFn enc = nullptr;
    static void *pB = nullptr, *pQ = nullptr;
    if (!enc) {
        void* fn = nullptr;
        cudaDriverEntryPointQueryResult qr;
        cudaGetDriverEntryPoint("cuTensorMapEncodeTiled", &fn, cudaEnableDefault, &qr);
        enc = (EncodeTiledFn)fn;
        cudaGetSymbolAddress(&pB, g_bT);
        cudaGetSymbolAddress(&pQ, g_qkv);
        cudaFuncSetAttribute(k1_qkv, cudaFuncAttributeMaxDynamicSharedMemorySize, K1_SMEM);
        cudaFuncSetAttribute(k2_attn, cudaFuncAttributeMaxDynamicSharedMemorySize, K2_SMEM);
        cudaFuncSetAttribute(k3_out, cudaFuncAttributeMaxDynamicSharedMemorySize, K3_SMEM);
    }
    CUtensorMap tmX, tmW, tmXs, tmB, tmOut, tmQ8, tmQ4, tmQ2, tmQ1;
    make_qkv_map(enc, &tmQ8, pQ, 8); make_qkv_map(enc, &tmQ4, pQ, 4); make_qkv_map(enc, &tmQ2, pQ, 2); make_qkv_map(enc, &tmQ1, pQ, 1);
    make_map(enc, &tmX, d_in[0], DM, SEQ, 64, 128, CU_TENSOR_MAP_SWIZZLE_128B);
    make_map(enc, &tmW, d_in[1], 3 * DM, DM, 64, 64, CU_TENSOR_MAP_SWIZZLE_128B);
    make_map(enc, &tmXs, d_in[0], DM, SEQ, 72, 128, CU_TENSOR_MAP_SWIZZLE_NONE);
    make_map(enc, &tmB, pB, SEQ / 2, 2 * DM, 64, 144, CU_TENSOR_MAP_SWIZZLE_128B);
    make_map(enc, &tmOut, d_out, DM, SEQ, 72, 64, CU_TENSOR_MAP_SWIZZLE_NONE);

    K1Params p1;
    p1.x = (bp)d_in[0]; p1.wo = (bp)d_in[2];
    p1.a_re = (bp)d_in[4]; p1.a_im = (bp)d_in[5]; p1.b_re = (bp)d_in[6]; p1.b_im = (bp)d_in[7];
    p1.c_re = (bp)d_in[8]; p1.c_im = (bp)d_in[9]; p1.log_dt = (bp)d_in[10]; p1.gate_w = (bp)d_in[12];
    K2Params p2;
    p2.a_re = p1.a_re; p2.a_im = p1.a_im; p2.b_re = p1.b_re; p2.b_im = p1.b_im; p2.c_re = p1.c_re; p2.c_im = p1.c_im;
    p2.log_dt = (bp)d_in[10]; p2.dskip = (bp)d_in[11];

    cudaStream_t st = cudaStreamPerThread;
    launch(k1_qkv, 128, K1_THREADS, K1_SMEM, st, false, tmX, tmW, tmXs, tmQ8, tmQ4, tmQ2, tmQ1, p1);
    launch(k2_attn, 132, K2_THREADS, K2_SMEM, st, true, p2);
    launch(k3_out, 128, K3_THREADS, K3_SMEM, st, true, tmB, tmOut);
}
```
